```python
import torch

def _softmax(x, axis=-1):
    return torch.softmax(x, dim=axis)
def _gelu(x):
    return torch.nn.functional.gelu(x, approximate="tanh")
def _silu(x):
    return torch.nn.functional.silu(x)
def _sigmoid(x):
    return torch.sigmoid(x)
def _layernorm(x, axis=-1, eps=1e-5):
    m = x.mean(dim=axis, keepdim=True)
    v = x.var(dim=axis, keepdim=True, unbiased=False)
    return (x - m) / torch.sqrt(v + eps)
def _scatter_add(tgt, idx, src, axis=0):
    return tgt.clone().index_add_(axis, idx, src)
def _segment_sum(src, seg, n):
    out = torch.zeros((n,) + src.shape[1:], dtype=src.dtype)
    return out.index_add_(0, seg, src)
def _pad(x, pw):
    flat = tuple(v for pair in reversed(pw) for v in pair)
    return torch.nn.functional.pad(x, flat)

kernel_name = 'gated_mix__ssm_conv_s4__linear_attn_block__prompt'

def setup_inputs():

    _w = (lambda a: (lambda t: t.to(torch.bfloat16) if t.is_floating_point() else t)(torch.as_tensor(a)))
    def _A_setup():
        B, L, D, N = 1, 2048, 640, 128
        A_re = -(lambda _x: torch.exp(torch.as_tensor(_x)))((lambda *s: torch.randn(*s, dtype=torch.bfloat16) * 3.2)(D, N))
        A_im = torch.pi * (lambda *s: torch.randn(*s, dtype=torch.bfloat16) * 0.05)(D, N)
        B_re = (lambda *s: torch.randn(*s, dtype=torch.bfloat16) * 0.2)(D, N)
        B_im = (lambda *s: torch.randn(*s, dtype=torch.bfloat16) * 0.2)(D, N)
        C_re = (lambda *s: torch.randn(*s, dtype=torch.bfloat16) * 0.2)(D, N)
        C_im = (lambda *s: torch.randn(*s, dtype=torch.bfloat16) * 0.2)(D, N)
        log_dt = (lambda *s: torch.randn(*s, dtype=torch.bfloat16) * 0.05)(D) * 0.5 - 4.0
        Dskip = (lambda *s: torch.randn(*s, dtype=torch.bfloat16) * 0.05)(D)
        return {
            "u": _w((lambda *s: torch.randn(*s, dtype=torch.bfloat16) * 0.05)(B, L, D)),
            "A_re": _w(A_re),
            "A_im": _w(A_im),
            "B_re": _w(B_re),
            "B_im": _w(B_im),
            "C_re": _w(C_re),
            "C_im": _w(C_im),
            "log_dt": _w(log_dt),
            "Dskip": _w(Dskip),
        }
    _A_in = _A_setup()

    def _B_setup():
        B, S, D = 1, 2048, 640
        return {
            "x": _w((lambda *s: torch.randn(*s, dtype=torch.bfloat16) * 0.05)(B, S, D)),
            "wqkv": _w((lambda *s: torch.randn(*s, dtype=torch.bfloat16) * 0.8)(D, 3 * D)),
            "wo": _w((lambda *s: torch.randn(*s, dtype=torch.bfloat16) * 0.05)(D, D)),
        }
    _B_in = _B_setup()

    return {
        "A_u": _A_in["u"],
        "A_A_re": _A_in["A_re"],
        "A_A_im": _A_in["A_im"],
        "A_B_re": _A_in["B_re"],
        "A_B_im": _A_in["B_im"],
        "A_C_re": _A_in["C_re"],
        "A_C_im": _A_in["C_im"],
        "A_log_dt": _A_in["log_dt"],
        "A_Dskip": _A_in["Dskip"],
        "B_x": _B_in["x"],
        "B_wqkv": _B_in["wqkv"],
        "B_wo": _B_in["wo"],
        "gate_w": _w((lambda *s: torch.randn(*s, dtype=torch.bfloat16) * 0.05)(640) * 16.0),
    }

def reference(A_u, A_A_re, A_A_im, A_B_re, A_B_im, A_C_re, A_C_im, A_log_dt, A_Dskip, B_x, B_wqkv, B_wo, gate_w):
    def _A_ref(u, A_re, A_im, B_re, B_im, C_re, C_im, log_dt, Dskip):
        Bsz, L, D = u.shape
        dt = torch.exp(log_dt)[:, None]
        A = A_re + 1j * A_im
        Bc = B_re + 1j * B_im
        Cc = C_re + 1j * C_im
        logdA = dt * A
        dB = dt * Bc
        l = (lambda x, dt: x.to(dt))(torch.arange(L), A_re.dtype)
        P = torch.exp(logdA[:, :, None] * l[None, None, :])
        K = torch.einsum("dn,dnl,dn->dl", Cc, P, dB).real
        L2 = 2 * L
        Kp = _pad(K, ((0, 0), (0, L)))
        up = (lambda x, *d: x.permute(*d))(u, 0, 2, 1)
        up = _pad(up, ((0, 0), (0, 0), (0, L)))
        Kf = (lambda x, axes=(-2,-1): torch.fft.rfft2(x.float(), dim=axes))(Kp[:, None, :], axes=(-2, -1))
        Uf = (lambda x, axes=(-2,-1): torch.fft.rfft2(x.float(), dim=axes))(up[:, :, None, :], axes=(-2, -1))
        Yf = Uf * Kf[None, :, :, :]
        y = (lambda x, s, axes=(-2,-1): torch.fft.irfft2(x, s=s, dim=axes).to(torch.bfloat16))(Yf, (1, L2), axes=(-2, -1))[:, :, 0, :L]
        y = (lambda x, *d: x.permute(*d))(y, 0, 2, 1) + u * Dskip[None, None, :]
        return y

    def _B_ref(x, wqkv, wo):
        B, S, D = x.shape
        H = 32; Dh = D // H
        qkv = (lambda x, *d: x.permute(*d))((x @ wqkv).reshape(B, S, 3, H, Dh), 2, 0, 3, 1, 4)
        q, k, v = qkv[0], qkv[1], qkv[2]
        phi = lambda t: torch.where(t > 0, t + 1, torch.exp(t)) + 1e-6
        pq, pk = phi(q), phi(k)
        kv = torch.einsum("bhsd,bhse->bhde", pk, v)
        z = torch.einsum("bhsd->bhd", pk)
        num = torch.einsum("bhqd,bhde->bhqe", pq, kv)
        den = torch.einsum("bhqd,bhd->bhq", pq, z)[..., None] + 1e-6
        o = num / den
        return (lambda x, *d: x.permute(*d))(o, 0, 2, 1, 3).reshape(B, S, D) @ wo

    x = A_u
    g = _sigmoid((x * gate_w).sum(-1, keepdims=True))
    a = _A_ref(x, A_A_re, A_A_im, A_B_re, A_B_im, A_C_re, A_C_im, A_log_dt, A_Dskip)
    b = _B_ref(x, B_wqkv, B_wo)
    return g * a + (1 - g) * b
```

```cpp
#include <cuda_runtime.h>
#include <cuda_bf16.h>
#include <cuda.h>
#include <stdint.h>

namespace {

constexpr int SEQ = 2048, DM = 640;
constexpr int NTHREADS = 512;
constexpr int ST_BYTES = 47104;
__host__ __device__ constexpr int stage_off(int s) { return s == 2 ? 141312 : (s == 3 ? 94208 : s * ST_BYTES); }
constexpr int OFF_PK = 0, OFF_V = 20480, OFF_ONES = 40960;
constexpr int OFF_WO = 38912;
constexpr int OFF_KVB = 0;
constexpr int OFF_KVST = 45056;
constexpr int OFF_OST = 18432;
constexpr int OFF_TAB = 141312;
constexpr int TAB_BYTES = 8448;
constexpr int OFF_AT = 141312;
constexpr int OFF_UT = 188416;
constexpr int UT_PLANE = 656, UT_BYTES = 8 * UT_PLANE;
constexpr int OFF_KB = OFF_UT + 5 * UT_BYTES;
constexpr int KB_BYTES = 1296;
constexpr int OFF_K4 = OFF_KB + 5 * KB_BYTES;
constexpr int OFF_CST = OFF_K4 + 648 * 4;
constexpr int OFF_MISC = 231936;
constexpr int SMEM_BYTES = OFF_MISC + 512;
static_assert(OFF_CST + 8192 <= OFF_MISC, "smem map");
constexpr int B_FULL = 0, B_TABFREE = 32, B_WO = 64, B_GATE = 80, B_AT = 88, B_CONV = 96;
constexpr int M_EPOCH = 160, M_STG = 176;
constexpr int SPIN_LIMIT = 1 << 22;

constexpr int KV_STRIDE = 1792;
__device__ float g_kvacc[2 * 8 * KV_STRIDE];
__device__ unsigned g_cnt[3 * 16 * 32];
__device__ __nv_bfloat16 g_gate[SEQ];
__device__ __nv_bfloat16 g_o[SEQ * DM];
__device__ __nv_bfloat16 g_aT[DM * SEQ];

__device__ __forceinline__ uint32_t smem_u32(const void* p) { return (uint32_t)__cvta_generic_to_shared(p); }
__device__ __forceinline__ void mbar_init(uint32_t bar, int cnt) { asm volatile("mbarrier.init.shared::cta.b64 [%0], %1;" :: "r"(bar), "r"(cnt)); }
__device__ __forceinline__ void mbar_expect_tx(uint32_t bar, uint32_t bytes) { asm volatile("mbarrier.arrive.expect_tx.shared::cta.b64 _, [%0], %1;" :: "r"(bar), "r"(bytes) : "memory"); }
__device__ __forceinline__ void mbar_arrive(uint32_t bar) { asm volatile("mbarrier.arrive.shared::cta.b64 _, [%0];" :: "r"(bar) : "memory"); }
__device__ __forceinline__ bool mbar_try(uint32_t bar, uint32_t parity) {
    uint32_t ok;
    asm volatile("{\n.reg .pred p;\nmbarrier.try_wait.parity.shared::cta.b64 p, [%1], %2;\nselp.u32 %0, 1, 0, p;\n}" : "=r"(ok) : "r"(bar), "r"(parity) : "memory");
    return ok;
}
__device__ __forceinline__ void mbar_wait(uint32_t bar, uint32_t parity) {
    for (int i = 0; i < SPIN_LIMIT; i++) { if (mbar_try(bar, parity)) return; }
    __trap();
}
__device__ __forceinline__ void tma2d(uint32_t dst, const CUtensorMap* m, int c0, int c1, uint32_t bar) {
    asm volatile("cp.async.bulk.tensor.2d.shared::cluster.global.mbarrier::complete_tx::bytes [%0], [%1, {%3, %4}], [%2];" :: "r"(dst), "l"(m), "r"(bar), "r"(c0), "r"(c1) : "memory");
}
__device__ __forceinline__ void tma3d(uint32_t dst, const CUtensorMap* m, int c0, int c1, int c2, uint32_t bar) {
    asm volatile("cp.async.bulk.tensor.3d.shared::cluster.global.mbarrier::complete_tx::bytes [%0], [%1, {%3, %4, %5}], [%2];" :: "r"(dst), "l"(m), "r"(bar), "r"(c0), "r"(c1), "r"(c2) : "memory");
}
__device__ __forceinline__ void tma5d(uint32_t dst, const CUtensorMap* m, int c0, uint32_t bar) {
    asm volatile("cp.async.bulk.tensor.5d.shared::cluster.global.mbarrier::complete_tx::bytes [%0], [%1, {%3, %4, %4, %4, %4}], [%2];" :: "r"(dst), "l"(m), "r"(bar), "r"(c0), "r"(0) : "memory");
}
__device__ __forceinline__ void tma_store2d(const CUtensorMap* m, uint32_t src, int c0, int c1) {
    asm volatile("cp.async.bulk.tensor.2d.global.shared::cta.bulk_group [%0, {%2, %3}], [%1];" :: "l"(m), "r"(src), "r"(c0), "r"(c1) : "memory");
}
__device__ __forceinline__ void bulk_load(uint32_t dst, const void* src, uint32_t bytes, uint32_t bar) {
    asm volatile("cp.async.bulk.shared::cluster.global.mbarrier::complete_tx::bytes [%0], [%1], %2, [%3];" :: "r"(dst), "l"(src), "r"(bytes), "r"(bar) : "memory");
}
__device__ __forceinline__ void bulk_commit() { asm volatile("cp.async.bulk.commit_group;" ::: "memory"); }
__device__ __forceinline__ void bulk_wait0() { asm volatile("cp.async.bulk.wait_group 0;" ::: "memory"); }
__device__ __forceinline__ void fence_async() { asm volatile("fence.proxy.async.shared::cta;" ::: "memory"); }
__device__ __forceinline__ void fence_async_global() { asm volatile("fence.proxy.async.global;" ::: "memory"); }
__device__ __forceinline__ void wg_fence() { asm volatile("wgmma.fence.sync.aligned;" ::: "memory"); }
__device__ __forceinline__ void wg_commit() { asm volatile("wgmma.commit_group.sync.aligned;" ::: "memory"); }
template <int N> __device__ __forceinline__ void wg_wait() { asm volatile("wgmma.wait_group.sync.aligned %0;" :: "n"(N) : "memory"); }
__device__ __forceinline__ uint64_t make_desc(uint32_t addr, uint32_t lbo, uint32_t sbo, int swz) {
    return (uint64_t)((addr & 0x3FFFF) >> 4) | ((uint64_t)(lbo >> 4) << 16) | ((uint64_t)(sbo >> 4) << 32) | ((uint64_t)swz << 62);
}
__device__ __forceinline__ void bar_sync(int id, int n) { asm volatile("bar.sync %0, %1;" :: "r"(id), "r"(n) : "memory"); }
__device__ __forceinline__ uint32_t pack_bf16(float lo, float hi) {
    uint32_t r; asm("cvt.rn.bf16x2.f32 %0, %1, %2;" : "=r"(r) : "f"(hi), "f"(lo)); return r;
}
__device__ __forceinline__ float bf_lo(uint32_t v) { return __uint_as_float(v << 16); }
__device__ __forceinline__ float bf_hi(uint32_t v) { return __uint_as_float(v & 0xFFFF0000u); }
__device__ __forceinline__ float ex2f(float x) { float r; asm("ex2.approx.ftz.f32 %0, %1;" : "=f"(r) : "f"(x)); return r; }
__device__ __forceinline__ uint32_t hmul2_rn(uint32_t a, uint32_t b) { uint32_t r; asm("mul.rn.bf16x2 %0, %1, %2;" : "=r"(r) : "r"(a), "r"(b)); return r; }
__device__ __forceinline__ uint32_t hadd2_rn(uint32_t a, uint32_t b) { uint32_t r; asm("add.rn.bf16x2 %0, %1, %2;" : "=r"(r) : "r"(a), "r"(b)); return r; }
__device__ __forceinline__ uint32_t hsub2_rn(uint32_t a, uint32_t b) { uint32_t r; asm("sub.rn.bf16x2 %0, %1, %2;" : "=r"(r) : "r"(a), "r"(b)); return r; }
__device__ __forceinline__ void stsm_x4(uint32_t addr, uint32_t r0, uint32_t r1, uint32_t r2, uint32_t r3) {
    asm volatile("stmatrix.sync.aligned.m8n8.x4.shared.b16 [%0], {%1, %2, %3, %4};" :: "r"(addr), "r"(r0), "r"(r1), "r"(r2), "r"(r3) : "memory");
}
__device__ __forceinline__ void stsm_x4_t(uint32_t addr, uint32_t r0, uint32_t r1, uint32_t r2, uint32_t r3) {
    asm volatile("stmatrix.sync.aligned.m8n8.x4.trans.shared.b16 [%0], {%1, %2, %3, %4};" :: "r"(addr), "r"(r0), "r"(r1), "r"(r2), "r"(r3) : "memory");
}
__device__ __forceinline__ void ldsm_x4_t(uint32_t addr, uint32_t& r0, uint32_t& r1, uint32_t& r2, uint32_t& r3) {
    asm volatile("ldmatrix.sync.aligned.m8n8.x4.trans.shared.b16 {%0, %1, %2, %3}, [%4];" : "=r"(r0), "=r"(r1), "=r"(r2), "=r"(r3) : "r"(addr) : "memory");
}
__device__ __forceinline__ void sts128(uint32_t addr, uint32_t a, uint32_t b, uint32_t c, uint32_t d) {
    asm volatile("st.shared.v4.b32 [%0], {%1, %2, %3, %4};" :: "r"(addr), "r"(a), "r"(b), "r"(c), "r"(d) : "memory");
}
__device__ __forceinline__ uint4 lds128(uint32_t addr) {
    uint4 v; asm volatile("ld.shared.v4.b32 {%0, %1, %2, %3}, [%4];" : "=r"(v.x), "=r"(v.y), "=r"(v.z), "=r"(v.w) : "r"(addr) : "memory"); return v;
}
__device__ __forceinline__ uint2 lds64(uint32_t addr) {
    uint2 v; asm volatile("ld.shared.v2.b32 {%0, %1}, [%2];" : "=r"(v.x), "=r"(v.y) : "r"(addr) : "memory"); return v;
}
__device__ __forceinline__ uint32_t lds32(uint32_t addr) {
    uint32_t v; asm volatile("ld.shared.b32 %0, [%1];" : "=r"(v) : "r"(addr) : "memory"); return v;
}
__device__ __forceinline__ void sts32(uint32_t addr, uint32_t v) { asm volatile("st.shared.b32 [%0], %1;" :: "r"(addr), "r"(v) : "memory"); }
__device__ __forceinline__ uint4 ldg128_cg(const void* p) {
    uint4 v; asm volatile("ld.global.cg.v4.b32 {%0, %1, %2, %3}, [%4];" : "=r"(v.x), "=r"(v.y), "=r"(v.z), "=r"(v.w) : "l"(p) : "memory"); return v;
}
__device__ __forceinline__ unsigned ld_acquire(const unsigned* p) {
    unsigned v; asm volatile("ld.acquire.gpu.global.u32 %0, [%1];" : "=r"(v) : "l"(p) : "memory"); return v;
}
__device__ __forceinline__ unsigned ld_relaxed(const unsigned* p) {
    unsigned v; asm volatile("ld.relaxed.gpu.global.u32 %0, [%1];" : "=r"(v) : "l"(p) : "memory"); return v;
}
__device__ __forceinline__ void red_release(unsigned* p, unsigned v) { asm volatile("red.release.gpu.global.add.u32 [%0], %1;" :: "l"(p), "r"(v) : "memory"); }
__device__ __forceinline__ void wait_counter(const unsigned* p, unsigned target) {
    for (int i = 0; i < SPIN_LIMIT; i++) { if ((int)(ld_acquire(p) - target) >= 0) return; }
    __trap();
}
__device__ __forceinline__ void red_add_v2(float* p, float a, float b) { asm volatile("red.global.add.v2.f32 [%0], {%1, %2};" :: "l"(p), "f"(a), "f"(b) : "memory"); }
__device__ __forceinline__ void red_add_f(float* p, float a) { asm volatile("red.global.add.f32 [%0], %1;" :: "l"(p), "f"(a) : "memory"); }
__device__ __forceinline__ void mma16816(float (&d)[4], uint32_t a0, uint32_t a1, uint32_t a2, uint32_t a3, uint32_t b0, uint32_t b1) {
    asm volatile("mma.sync.aligned.m16n8k16.row.col.f32.bf16.bf16.f32 {%0,%1,%2,%3}, {%4,%5,%6,%7}, {%8,%9}, {%0,%1,%2,%3};"
                 : "+f"(d[0]), "+f"(d[1]), "+f"(d[2]), "+f"(d[3]) : "r"(a0), "r"(a1), "r"(a2), "r"(a3), "r"(b0), "r"(b1));
}
__device__ __forceinline__ uint32_t atom_inc_cta(uint32_t addr) {
    uint32_t v; asm volatile("atom.acq_rel.cta.shared.add.u32 %0, [%1], 1;" : "=r"(v) : "r"(addr) : "memory"); return v;
}
__device__ __forceinline__ uint32_t phi2(float a, float b) {
    const uint32_t t2 = pack_bf16(a, b);
    const uint32_t e2 = pack_bf16(ex2f(bf_lo(t2) * 1.4426950408889634f), ex2f(bf_hi(t2) * 1.4426950408889634f));
    const uint32_t p2 = hadd2_rn(t2, 0x3F803F80u);
    uint32_t m; asm("set.gt.u32.bf16x2 %0, %1, %2;" : "=r"(m) : "r"(t2), "r"(0u));
    return hadd2_rn((p2 & m) | (e2 & ~m), 0x35863586u);
}
__device__ __forceinline__ float rcp_fast(float x) { float r; asm("rcp.approx.ftz.f32 %0, %1;" : "=f"(r) : "f"(x)); return r; }
__device__ __forceinline__ void sts64(uint32_t addr, uint32_t a, uint32_t b) { asm volatile("st.shared.v2.b32 [%0], {%1, %2};" :: "r"(addr), "r"(a), "r"(b) : "memory"); }
__device__ __forceinline__ void sts64f(uint32_t addr, float a, float b) { asm volatile("st.shared.v2.f32 [%0], {%1, %2};" :: "r"(addr), "f"(a), "f"(b) : "memory"); }
__device__ __forceinline__ void sts32f(uint32_t addr, float a) { asm volatile("st.shared.f32 [%0], %1;" :: "r"(addr), "f"(a) : "memory"); }
__device__ __forceinline__ void sts16(uint32_t addr, uint32_t v) { asm volatile("st.shared.b16 [%0], %1;" :: "r"(addr), "h"((unsigned short)v) : "memory"); }
__device__ __forceinline__ void bulk_reduce_add_f32(void* dst, uint32_t src, uint32_t bytes) {
    asm volatile("cp.reduce.async.bulk.global.shared::cta.bulk_group.add.f32 [%0], [%1], %2;" :: "l"(dst), "r"(src), "r"(bytes) : "memory");
}
__device__ __forceinline__ void ldsm_x4(uint32_t addr, uint32_t& r0, uint32_t& r1, uint32_t& r2, uint32_t& r3) {
    asm volatile("ldmatrix.sync.aligned.m8n8.x4.shared.b16 {%0, %1, %2, %3}, [%4];" : "=r"(r0), "=r"(r1), "=r"(r2), "=r"(r3) : "r"(addr) : "memory");
}
__device__ __forceinline__ void ldsm_x2(uint32_t addr, uint32_t& r0, uint32_t& r1) {
    asm volatile("ldmatrix.sync.aligned.m8n8.x2.shared.b16 {%0, %1}, [%2];" : "=r"(r0), "=r"(r1) : "r"(addr) : "memory");
}
__device__ __forceinline__ float4 lds128f(uint32_t addr) {
    float4 v; asm volatile("ld.shared.v4.f32 {%0, %1, %2, %3}, [%4];" : "=f"(v.x), "=f"(v.y), "=f"(v.z), "=f"(v.w) : "r"(addr) : "memory"); return v;
}
__device__ __forceinline__ float lds32f(uint32_t addr) { float v; asm volatile("ld.shared.f32 %0, [%1];" : "=f"(v) : "r"(addr) : "memory"); return v; }
__device__ __forceinline__ void sts128f(uint32_t addr, float a, float b, float c, float d) {
    asm volatile("st.shared.v4.f32 [%0], {%1, %2, %3, %4};" :: "r"(addr), "f"(a), "f"(b), "f"(c), "f"(d) : "memory");
}
__device__ __forceinline__ void stg128(void* p, uint4 v) { asm volatile("st.global.v4.b32 [%0], {%1, %2, %3, %4};" :: "l"(p), "r"(v.x), "r"(v.y), "r"(v.z), "r"(v.w) : "memory"); }
__device__ __forceinline__ void wgmma_n192_ss_ta0_tb1(float (&d)[96], uint64_t descA, uint64_t descB, int scaleD) {
  asm volatile("{\n.reg .pred p;\n"
    "setp.ne.b32 p, %98, 0;\n"
    "wgmma.mma_async.sync.aligned.m64n192k16.f32.bf16.bf16 "
    "{%0, %1, %2, %3, %4, %5, %6, %7, %8, %9, %10, %11, %12, %13, %14, %15, %16, %17, %18, %19, %20, %21, %22, %23, %24, %25, %26, %27, %28, %29, %30, %31, %32, %33, %34, %35, %36, %37, %38, %39, %40, %41, %42, %43, %44, %45, %46, %47, %48, %49, %50, %51, %52, %53, %54, %55, %56, %57, %58, %59, %60, %61, %62, %63, %64, %65, %66, %67, %68, %69, %70, %71, %72, %73, %74, %75, %76, %77, %78, %79, %80, %81, %82, %83, %84, %85, %86, %87, %88, %89, %90, %91, %92, %93, %94, %95}, "
    "%96, %97, p, 1, 1, 0, 1;\n}\n"
    : "+f"(d[0]), "+f"(d[1]), "+f"(d[2]), "+f"(d[3]), "+f"(d[4]), "+f"(d[5]), "+f"(d[6]), "+f"(d[7]), "+f"(d[8]), "+f"(d[9]), "+f"(d[10]), "+f"(d[11]), "+f"(d[12]), "+f"(d[13]), "+f"(d[14]), "+f"(d[15]), "+f"(d[16]), "+f"(d[17]), "+f"(d[18]), "+f"(d[19]), "+f"(d[20]), "+f"(d[21]), "+f"(d[22]), "+f"(d[23]), "+f"(d[24]), "+f"(d[25]), "+f"(d[26]), "+f"(d[27]), "+f"(d[28]), "+f"(d[29]), "+f"(d[30]), "+f"(d[31]), "+f"(d[32]), "+f"(d[33]), "+f"(d[34]), "+f"(d[35]), "+f"(d[36]), "+f"(d[37]), "+f"(d[38]), "+f"(d[39]), "+f"(d[40]), "+f"(d[41]), "+f"(d[42]), "+f"(d[43]), "+f"(d[44]), "+f"(d[45]), "+f"(d[46]), "+f"(d[47]), "+f"(d[48]), "+f"(d[49]), "+f"(d[50]), "+f"(d[51]), "+f"(d[52]), "+f"(d[53]), "+f"(d[54]), "+f"(d[55]), "+f"(d[56]), "+f"(d[57]), "+f"(d[58]), "+f"(d[59]), "+f"(d[60]), "+f"(d[61]), "+f"(d[62]), "+f"(d[63]), "+f"(d[64]), "+f"(d[65]), "+f"(d[66]), "+f"(d[67]), "+f"(d[68]), "+f"(d[69]), "+f"(d[70]), "+f"(d[71]), "+f"(d[72]), "+f"(d[73]), "+f"(d[74]), "+f"(d[75]), "+f"(d[76]), "+f"(d[77]), "+f"(d[78]), "+f"(d[79]), "+f"(d[80]), "+f"(d[81]), "+f"(d[82]), "+f"(d[83]), "+f"(d[84]), "+f"(d[85]), "+f"(d[86]), "+f"(d[87]), "+f"(d[88]), "+f"(d[89]), "+f"(d[90]), "+f"(d[91]), "+f"(d[92]), "+f"(d[93]), "+f"(d[94]), "+f"(d[95])
    : "l"(descA), "l"(descB), "r"(scaleD));
}
__device__ __forceinline__ void wgmma_n48_ss_ta0_tb1(float (&d)[24], uint64_t descA, uint64_t descB, int scaleD) {
  asm volatile("{\n.reg .pred p;\n"
    "setp.ne.b32 p, %26, 0;\n"
    "wgmma.mma_async.sync.aligned.m64n48k16.f32.bf16.bf16 "
    "{%0, %1, %2, %3, %4, %5, %6, %7, %8, %9, %10, %11, %12, %13, %14, %15, %16, %17, %18, %19, %20, %21, %22, %23}, "
    "%24, %25, p, 1, 1, 0, 1;\n}\n"
    : "+f"(d[0]), "+f"(d[1]), "+f"(d[2]), "+f"(d[3]), "+f"(d[4]), "+f"(d[5]), "+f"(d[6]), "+f"(d[7]), "+f"(d[8]), "+f"(d[9]), "+f"(d[10]), "+f"(d[11]), "+f"(d[12]), "+f"(d[13]), "+f"(d[14]), "+f"(d[15]), "+f"(d[16]), "+f"(d[17]), "+f"(d[18]), "+f"(d[19]), "+f"(d[20]), "+f"(d[21]), "+f"(d[22]), "+f"(d[23])
    : "l"(descA), "l"(descB), "r"(scaleD));
}
__device__ __forceinline__ void wgmma_n88_ss_ta1_tb1(float (&d)[44], uint64_t descA, uint64_t descB, int scaleD) {
  asm volatile("{\n.reg .pred p;\n"
    "setp.ne.b32 p, %46, 0;\n"
    "wgmma.mma_async.sync.aligned.m64n88k16.f32.bf16.bf16 "
    "{%0, %1, %2, %3, %4, %5, %6, %7, %8, %9, %10, %11, %12, %13, %14, %15, %16, %17, %18, %19, %20, %21, %22, %23, %24, %25, %26, %27, %28, %29, %30, %31, %32, %33, %34, %35, %36, %37, %38, %39, %40, %41, %42, %43}, "
    "%44, %45, p, 1, 1, 1, 1;\n}\n"
    : "+f"(d[0]), "+f"(d[1]), "+f"(d[2]), "+f"(d[3]), "+f"(d[4]), "+f"(d[5]), "+f"(d[6]), "+f"(d[7]), "+f"(d[8]), "+f"(d[9]), "+f"(d[10]), "+f"(d[11]), "+f"(d[12]), "+f"(d[13]), "+f"(d[14]), "+f"(d[15]), "+f"(d[16]), "+f"(d[17]), "+f"(d[18]), "+f"(d[19]), "+f"(d[20]), "+f"(d[21]), "+f"(d[22]), "+f"(d[23]), "+f"(d[24]), "+f"(d[25]), "+f"(d[26]), "+f"(d[27]), "+f"(d[28]), "+f"(d[29]), "+f"(d[30]), "+f"(d[31]), "+f"(d[32]), "+f"(d[33]), "+f"(d[34]), "+f"(d[35]), "+f"(d[36]), "+f"(d[37]), "+f"(d[38]), "+f"(d[39]), "+f"(d[40]), "+f"(d[41]), "+f"(d[42]), "+f"(d[43])
    : "l"(descA), "l"(descB), "r"(scaleD));
}
__device__ __forceinline__ void wgmma_n88_rs_ta0_tb1(float (&d)[44], uint32_t a0, uint32_t a1, uint32_t a2, uint32_t a3, uint64_t descB, int scaleD) {
  asm volatile("{\n.reg .pred p;\n"
    "setp.ne.b32 p, %49, 0;\n"
    "wgmma.mma_async.sync.aligned.m64n88k16.f32.bf16.bf16 "
    "{%0, %1, %2, %3, %4, %5, %6, %7, %8, %9, %10, %11, %12, %13, %14, %15, %16, %17, %18, %19, %20, %21, %22, %23, %24, %25, %26, %27, %28, %29, %30, %31, %32, %33, %34, %35, %36, %37, %38, %39, %40, %41, %42, %43}, "
    "{%44, %45, %46, %47}, %48, p, 1, 1, 1;\n}\n"
    : "+f"(d[0]), "+f"(d[1]), "+f"(d[2]), "+f"(d[3]), "+f"(d[4]), "+f"(d[5]), "+f"(d[6]), "+f"(d[7]), "+f"(d[8]), "+f"(d[9]), "+f"(d[10]), "+f"(d[11]), "+f"(d[12]), "+f"(d[13]), "+f"(d[14]), "+f"(d[15]), "+f"(d[16]), "+f"(d[17]), "+f"(d[18]), "+f"(d[19]), "+f"(d[20]), "+f"(d[21]), "+f"(d[22]), "+f"(d[23]), "+f"(d[24]), "+f"(d[25]), "+f"(d[26]), "+f"(d[27]), "+f"(d[28]), "+f"(d[29]), "+f"(d[30]), "+f"(d[31]), "+f"(d[32]), "+f"(d[33]), "+f"(d[34]), "+f"(d[35]), "+f"(d[36]), "+f"(d[37]), "+f"(d[38]), "+f"(d[39]), "+f"(d[40]), "+f"(d[41]), "+f"(d[42]), "+f"(d[43])
    : "r"(a0), "r"(a1), "r"(a2), "r"(a3), "l"(descB), "r"(scaleD));
}
__device__ __forceinline__ void wgmma_n80_rs_ta0_tb1(float (&d)[40], uint32_t a0, uint32_t a1, uint32_t a2, uint32_t a3, uint64_t descB, int scaleD) {
  asm volatile("{\n.reg .pred p;\n"
    "setp.ne.b32 p, %45, 0;\n"
    "wgmma.mma_async.sync.aligned.m64n80k16.f32.bf16.bf16 "
    "{%0, %1, %2, %3, %4, %5, %6, %7, %8, %9, %10, %11, %12, %13, %14, %15, %16, %17, %18, %19, %20, %21, %22, %23, %24, %25, %26, %27, %28, %29, %30, %31, %32, %33, %34, %35, %36, %37, %38, %39}, "
    "{%40, %41, %42, %43}, %44, p, 1, 1, 1;\n}\n"
    : "+f"(d[0]), "+f"(d[1]), "+f"(d[2]), "+f"(d[3]), "+f"(d[4]), "+f"(d[5]), "+f"(d[6]), "+f"(d[7]), "+f"(d[8]), "+f"(d[9]), "+f"(d[10]), "+f"(d[11]), "+f"(d[12]), "+f"(d[13]), "+f"(d[14]), "+f"(d[15]), "+f"(d[16]), "+f"(d[17]), "+f"(d[18]), "+f"(d[19]), "+f"(d[20]), "+f"(d[21]), "+f"(d[22]), "+f"(d[23]), "+f"(d[24]), "+f"(d[25]), "+f"(d[26]), "+f"(d[27]), "+f"(d[28]), "+f"(d[29]), "+f"(d[30]), "+f"(d[31]), "+f"(d[32]), "+f"(d[33]), "+f"(d[34]), "+f"(d[35]), "+f"(d[36]), "+f"(d[37]), "+f"(d[38]), "+f"(d[39])
    : "r"(a0), "r"(a1), "r"(a2), "r"(a3), "l"(descB), "r"(scaleD));
}
__device__ __forceinline__ void wgmma_n32_rs_ta0_tb0(float (&d)[16], uint32_t a0, uint32_t a1, uint32_t a2, uint32_t a3, uint64_t descB, int scaleD) {
  asm volatile("{\n.reg .pred p;\n"
    "setp.ne.b32 p, %21, 0;\n"
    "wgmma.mma_async.sync.aligned.m64n32k16.f32.bf16.bf16 "
    "{%0, %1, %2, %3, %4, %5, %6, %7, %8, %9, %10, %11, %12, %13, %14, %15}, "
    "{%16, %17, %18, %19}, %20, p, 1, 1, 0;\n}\n"
    : "+f"(d[0]), "+f"(d[1]), "+f"(d[2]), "+f"(d[3]), "+f"(d[4]), "+f"(d[5]), "+f"(d[6]), "+f"(d[7]), "+f"(d[8]), "+f"(d[9]), "+f"(d[10]), "+f"(d[11]), "+f"(d[12]), "+f"(d[13]), "+f"(d[14]), "+f"(d[15])
    : "r"(a0), "r"(a1), "r"(a2), "r"(a3), "l"(descB), "r"(scaleD));
}
__device__ __forceinline__ void wgmma_n24_rs_ta0_tb0(float (&d)[12], uint32_t a0, uint32_t a1, uint32_t a2, uint32_t a3, uint64_t descB, int scaleD) {
  asm volatile("{\n.reg .pred p;\n"
    "setp.ne.b32 p, %17, 0;\n"
    "wgmma.mma_async.sync.aligned.m64n24k16.f32.bf16.bf16 "
    "{%0, %1, %2, %3, %4, %5, %6, %7, %8, %9, %10, %11}, "
    "{%12, %13, %14, %15}, %16, p, 1, 1, 0;\n}\n"
    : "+f"(d[0]), "+f"(d[1]), "+f"(d[2]), "+f"(d[3]), "+f"(d[4]), "+f"(d[5]), "+f"(d[6]), "+f"(d[7]), "+f"(d[8]), "+f"(d[9]), "+f"(d[10]), "+f"(d[11])
    : "r"(a0), "r"(a1), "r"(a2), "r"(a3), "l"(descB), "r"(scaleD));
}
__device__ __forceinline__ void wgmma_n16_rs_ta0_tb0(float (&d)[8], uint32_t a0, uint32_t a1, uint32_t a2, uint32_t a3, uint64_t descB, int scaleD) {
  asm volatile("{\n.reg .pred p;\n"
    "setp.ne.b32 p, %13, 0;\n"
    "wgmma.mma_async.sync.aligned.m64n16k16.f32.bf16.bf16 "
    "{%0, %1, %2, %3, %4, %5, %6, %7}, "
    "{%8, %9, %10, %11}, %12, p, 1, 1, 0;\n}\n"
    : "+f"(d[0]), "+f"(d[1]), "+f"(d[2]), "+f"(d[3]), "+f"(d[4]), "+f"(d[5]), "+f"(d[6]), "+f"(d[7])
    : "r"(a0), "r"(a1), "r"(a2), "r"(a3), "l"(descB), "r"(scaleD));
}
__device__ __forceinline__ void wgmma_n8_rs_ta0_tb0(float (&d)[4], uint32_t a0, uint32_t a1, uint32_t a2, uint32_t a3, uint64_t descB, int scaleD) {
  asm volatile("{\n.reg .pred p;\n"
    "setp.ne.b32 p, %9, 0;\n"
    "wgmma.mma_async.sync.aligned.m64n8k16.f32.bf16.bf16 "
    "{%0, %1, %2, %3}, "
    "{%4, %5, %6, %7}, %8, p, 1, 1, 0;\n}\n"
    : "+f"(d[0]), "+f"(d[1]), "+f"(d[2]), "+f"(d[3])
    : "r"(a0), "r"(a1), "r"(a2), "r"(a3), "l"(descB), "r"(scaleD));
}
__device__ __forceinline__ void wgmma_n80_ss_ta0_tb1(float (&d)[40], uint64_t descA, uint64_t descB, int scaleD) {
  asm volatile("{\n.reg .pred p;\n"
    "setp.ne.b32 p, %42, 0;\n"
    "wgmma.mma_async.sync.aligned.m64n80k16.f32.bf16.bf16 "
    "{%0, %1, %2, %3, %4, %5, %6, %7, %8, %9, %10, %11, %12, %13, %14, %15, %16, %17, %18, %19, %20, %21, %22, %23, %24, %25, %26, %27, %28, %29, %30, %31, %32, %33, %34, %35, %36, %37, %38, %39}, "
    "%40, %41, p, 1, 1, 0, 1;\n}\n"
    : "+f"(d[0]), "+f"(d[1]), "+f"(d[2]), "+f"(d[3]), "+f"(d[4]), "+f"(d[5]), "+f"(d[6]), "+f"(d[7]), "+f"(d[8]), "+f"(d[9]), "+f"(d[10]), "+f"(d[11]), "+f"(d[12]), "+f"(d[13]), "+f"(d[14]), "+f"(d[15]), "+f"(d[16]), "+f"(d[17]), "+f"(d[18]), "+f"(d[19]), "+f"(d[20]), "+f"(d[21]), "+f"(d[22]), "+f"(d[23]), "+f"(d[24]), "+f"(d[25]), "+f"(d[26]), "+f"(d[27]), "+f"(d[28]), "+f"(d[29]), "+f"(d[30]), "+f"(d[31]), "+f"(d[32]), "+f"(d[33]), "+f"(d[34]), "+f"(d[35]), "+f"(d[36]), "+f"(d[37]), "+f"(d[38]), "+f"(d[39])
    : "l"(descA), "l"(descB), "r"(scaleD));
}
struct Params {
    const __nv_bfloat16 *u, *A_re, *A_im, *B_re, *B_im, *C_re, *C_im, *log_dt, *Dskip, *gate_w;
    long long* tim;
};
#define TSTAMP(slot) do { } while (0)

__device__ __forceinline__ void issue_stage(const CUtensorMap* mA, const CUtensorMap* mB0, const CUtensorMap* mB1, uint32_t sb, int kb, int rb, int hg) {
    const int s = kb & 3;
    const uint32_t full = sb + OFF_MISC + B_FULL + 8 * s, st = sb + stage_off(s);
    mbar_expect_tx(full, ST_BYTES);
    tma2d(st, mA, kb * 64, rb * 128, full);
    tma3d(st + 16384, mB0, hg * 80, kb * 64, 0, full);
    tma3d(st + 16384 + 24576, mB1, hg * 80 + 64, kb * 64, 0, full);
}
__device__ __forceinline__ void consumer_role(const Params& P, const CUtensorMap* mA, const CUtensorMap* mB0, const CUtensorMap* mB1, const CUtensorMap* mWo,
                                              const CUtensorMap* mOut, uint32_t sb, int rb, int hg, unsigned ep) {
    const int tid = threadIdx.x, lane = tid & 31, warp = tid >> 5, wg = warp >> 2, w4 = warp & 3;
    const int g = lane >> 2, t = lane & 3;
    const uint32_t misc = sb + OFF_MISC;
    float acc[120];
    float (&acc192)[96] = *reinterpret_cast<float(*)[96]>(&acc[0]);
    float (&acc48)[24] = *reinterpret_cast<float(*)[24]>(&acc[96]);
#pragma unroll
    for (int i = 0; i < 120; i++) acc[i] = 0.f;
#pragma unroll 1
    for (int kb = 0; kb < 10; kb++) {
        const int s = kb & 3;
        mbar_wait(misc + B_FULL + 8 * s, (kb >> 2) & 1);
        const uint32_t st = sb + stage_off(s);
        const uint32_t sa = st + wg * 8192, sbb = st + 16384;
        wg_fence();
#pragma unroll
        for (int ks = 0; ks < 4; ks++) {
            const uint64_t da = make_desc(sa + ks * 32, 16, 1024, 1);
            wgmma_n192_ss_ta0_tb1(acc192, da, make_desc(sbb + ks * 2048, 8192, 1024, 1), 1);
            wgmma_n48_ss_ta0_tb1(acc48, da, make_desc(sbb + 24576 + ks * 512, 2048, 256, 3), 1);
        }
        wg_commit();
        if (kb > 0) {
            wg_wait<1>();
            if ((tid & 127) == 0) {
                if (kb <= 6) { if (atom_inc_cta(misc + M_STG + 4 * ((kb - 1) & 3)) & 1) issue_stage(mA, mB0, mB1, sb, kb + 3, rb, hg); }
                else if (kb == 7) mbar_arrive(misc + B_TABFREE);
            }
        }
    }
    wg_wait<0>();
    if (tid == 0) TSTAMP(1);
    {
        uint32_t pk[20], vv[20];
#pragma unroll
        for (int j = 0; j < 10; j++) {
            const int bk = j < 8 ? 32 + 4 * j : 104 + 4 * (j - 8);
            const int bv = j < 8 ? 64 + 4 * j : 112 + 4 * (j - 8);
            pk[2 * j] = phi2(acc[bk], acc[bk + 1]); pk[2 * j + 1] = phi2(acc[bk + 2], acc[bk + 3]);
            vv[2 * j] = pack_bf16(acc[bv], acc[bv + 1]); vv[2 * j + 1] = pack_bf16(acc[bv + 2], acc[bv + 3]);
        }
        bar_sync(1, 256);
        if (tid == 0) TSTAMP(10);
        const int m = lane >> 3, row = 64 * wg + 16 * w4 + (lane & 7) + 8 * (m & 1);
        const uint32_t off = row * 32 + (((m >> 1) ^ ((row >> 2) & 1)) << 4);
#pragma unroll
        for (int cg = 0; cg < 5; cg++) {
            stsm_x4(sb + OFF_PK + cg * 4096 + off, pk[4 * cg], pk[4 * cg + 1], pk[4 * cg + 2], pk[4 * cg + 3]);
            stsm_x4(sb + OFF_V + cg * 4096 + off, vv[4 * cg], vv[4 * cg + 1], vv[4 * cg + 2], vv[4 * cg + 3]);
        }
        const int r2 = tid >> 1, h = (tid & 1) ^ ((r2 >> 2) & 1);
        sts128(sb + OFF_ONES + tid * 16, h == 0 ? 0x00003F80u : 0u, 0u, 0u, 0u);
    }
    fence_async();
    bar_sync(1, 256);
    if (tid == 0) TSTAMP(11);
    float* kvg = g_kvacc + ((ep & 1) * 8 + hg) * KV_STRIDE;
    {
        float kv[44];
        wg_fence();
#pragma unroll
        for (int ks = 0; ks < 8; ks++)
            wgmma_n88_ss_ta1_tb1(kv, make_desc(sb + OFF_PK + wg * 16384 + ks * 512, 4096, 256, 3), make_desc(sb + OFF_V + ks * 512, 4096, 256, 3), ks > 0);
        wg_commit();
        wg_wait<0>();
        if (tid == 0) TSTAMP(13);
        if (wg == 0 || w4 == 0) {
#pragma unroll
            for (int hh = 0; hh < 2; hh++) {
                const int d = 64 * wg + 16 * w4 + g + 8 * hh, h = d / 20;
                const uint32_t rowp = sb + OFF_KVST + (d * 20 - 20 * h + 2 * t) * 4;
#pragma unroll
                for (int j = 0; j < 10; j++) {
                    const int c = 8 * j + 2 * t - 20 * h;
                    if (c >= 0 && c < 20) sts64f(rowp + 32 * j, kv[4 * j + 2 * hh], kv[4 * j + 2 * hh + 1]);
                }
                if (t == 0) sts32f(sb + OFF_KVST + (1600 + d) * 4, kv[40 + 2 * hh]);
            }
        }
    }
    fence_async();
    bar_sync(1, 256);
    if (tid == 0) {
        TSTAMP(15);
        bulk_reduce_add_f32(kvg, sb + OFF_KVST, 6720);
        bulk_commit();
        bulk_wait0();
        TSTAMP(16);
        red_release(&g_cnt[(0 * 16 + hg) * 32], 1u);
        TSTAMP(2);
    }
    uint32_t pq[20];
#pragma unroll
    for (int j = 0; j < 10; j++) {
        const int bq = j < 8 ? 4 * j : 96 + 4 * (j - 8);
        pq[2 * j] = phi2(acc[bq], acc[bq + 1]); pq[2 * j + 1] = phi2(acc[bq + 2], acc[bq + 3]);
    }
#pragma unroll
    for (int it = 0; it < 4; it++) { const int id = tid + 256 * it; if (id < 960) sts128(sb + OFF_KVB + id * 16, 0u, 0u, 0u, 0u); }
    if (tid == 0) TSTAMP(18);
    bar_sync(1, 256);
    if (tid == 0) TSTAMP(19);
    if (tid == 64) {
        mbar_expect_tx(misc + B_WO, 5 * 20480);
#pragma unroll
        for (int cg = 0; cg < 5; cg++) tma5d(sb + OFF_WO + cg * 20480, mWo, hg * 80 + 16 * cg, misc + B_WO);
    }
    if (lane == 0) wait_counter(&g_cnt[(0 * 16 + hg) * 32], (ep + 1) * 16);
    __syncwarp();
    if (tid == 0) TSTAMP(3);
    {
        const int d0 = tid / 5, u0 = tid - 5 * d0;
        const int id1 = tid + 256, d1 = id1 / 5, u1 = id1 - 5 * d1;
        const float4 v0 = __ldcg(reinterpret_cast<const float4*>(kvg) + tid);
        float4 v1 = make_float4(0.f, 0.f, 0.f, 0.f);
        if (tid < 144) v1 = __ldcg(reinterpret_cast<const float4*>(kvg) + id1);
        else if (tid < 224) v1.x = __ldcg(kvg + 1600 + tid - 144);
        {
            const int n = 20 * (d0 / 20) + 4 * u0;
            sts64(sb + OFF_KVB + (n >> 4) * 2560 + d0 * 32 + ((((n >> 3) & 1) ^ ((d0 >> 2) & 1)) << 4) + (n & 7) * 2, pack_bf16(v0.x, v0.y), pack_bf16(v0.z, v0.w));
        }
        if (tid < 144) {
            const int n = 20 * (d1 / 20) + 4 * u1;
            sts64(sb + OFF_KVB + (n >> 4) * 2560 + d1 * 32 + ((((n >> 3) & 1) ^ ((d1 >> 2) & 1)) << 4) + (n & 7) * 2, pack_bf16(v1.x, v1.y), pack_bf16(v1.z, v1.w));
        } else if (tid < 224) {
            const int d = tid - 144;
            sts16(sb + OFF_KVB + 5 * 2560 + d * 32 + (((d >> 2) & 1) << 4) + (d / 20) * 2, pack_bf16(v1.x, 0.f));
        }
    }
    if (tid == 0) TSTAMP(20);
    fence_async();
    bar_sync(1, 256);
    if (tid == 0) TSTAMP(21);
    {
        float nm[44];
        wg_fence();
#pragma unroll
        for (int ks = 0; ks < 5; ks++)
            wgmma_n88_rs_ta0_tb1(nm, pq[4 * ks], pq[4 * ks + 1], pq[4 * ks + 2], pq[4 * ks + 3], make_desc(sb + OFF_KVB + ks * 512, 2560, 256, 3), ks > 0);
        wg_commit();
        wg_wait<0>();
        if (tid == 0) TSTAMP(22);
        float rden[2][4];
#pragma unroll
        for (int hh = 0; hh < 2; hh++) {
#pragma unroll
            for (int h = 0; h < 4; h++) {
                float x = __shfl_sync(0xffffffffu, nm[40 + 2 * hh + (h & 1)], (lane & ~3) + (h >> 1));
                x = bf_lo(pack_bf16(x, 0.f)) + 1e-6f;
                rden[hh][h] = rcp_fast(bf_lo(pack_bf16(x, 0.f)));
            }
        }
        uint32_t ov[20];
#pragma unroll
        for (int j = 0; j < 10; j++) {
#pragma unroll
            for (int hh = 0; hh < 2; hh++) {
                float dn;
                if (j == 2) dn = t < 2 ? rden[hh][0] : rden[hh][1];
                else if (j == 7) dn = t < 2 ? rden[hh][2] : rden[hh][3];
                else dn = rden[hh][(8 * j) / 20];
                const uint32_t n2 = pack_bf16(nm[4 * j + 2 * hh], nm[4 * j + 2 * hh + 1]);
                ov[2 * j + hh] = pack_bf16(bf_lo(n2) * dn, bf_hi(n2) * dn);
            }
        }
        const int m = lane >> 3, row = 64 * wg + 16 * w4 + (lane & 7) + 8 * (m & 1);
#pragma unroll
        for (int cg = 0; cg < 5; cg++)
            stsm_x4(sb + OFF_OST + row * 160 + cg * 32 + (m >> 1) * 16, ov[4 * cg], ov[4 * cg + 1], ov[4 * cg + 2], ov[4 * cg + 3]);
        __syncwarp();
        const int r0 = 64 * wg + 16 * w4;
#pragma unroll
        for (int i = 0; i < 5; i++) {
            const int c = lane + 32 * i, r = c / 10, cc = c - 10 * r;
            stg128(g_o + (size_t)(128 * rb + r0 + r) * DM + 80 * hg + 8 * cc, lds128(sb + OFF_OST + (r0 + r) * 160 + cc * 16));
        }
    }
    if (tid == 0) TSTAMP(23);
    bar_sync(3 + wg, 128);
    if (tid == 0) TSTAMP(24);
    if ((tid & 127) == 0) {
        mbar_wait(misc + B_GATE, 0);
        red_release(&g_cnt[(1 * 16 + rb) * 32], 1u);
        if (tid == 0) TSTAMP(4);
    }
    if (lane == 0) wait_counter(&g_cnt[(1 * 16 + rb) * 32], (ep + 1) * 16);
    __syncwarp();
    if (tid == 0) TSTAMP(5);
    float fa[40];
    {
        const int row = 128 * rb + 64 * wg + 16 * w4 + g;
        const __nv_bfloat16* px = g_o + (size_t)row * DM + 8 * t;
        const __nv_bfloat16* py = px + 8 * DM;
#define CH(c) ((c) * 32)
        uint4 X[3][4], Y[3][4];
#pragma unroll
        for (int b = 0; b < 3; b++)
#pragma unroll
            for (int c = 0; c < 4; c++) { X[b][c] = ldg128_cg(px + CH(4 * b + c)); Y[b][c] = ldg128_cg(py + CH(4 * b + c)); }
        mbar_wait(misc + B_WO, 0);
        if (tid == 0) TSTAMP(30);
#pragma unroll
        for (int gi = 0; gi < 5; gi++) {
            const int b = gi % 3;
            wg_fence();
#pragma unroll
            for (int c = 0; c < 4; c++) {
                const uint32_t w = sb + OFF_WO + (4 * gi + c) * 1024;
                wgmma_n80_rs_ta0_tb1(fa, X[b][c].x, Y[b][c].x, X[b][c].y, Y[b][c].y, make_desc(w, 20480, 256, 3), (gi | c) != 0);
                wgmma_n80_rs_ta0_tb1(fa, X[b][c].z, Y[b][c].z, X[b][c].w, Y[b][c].w, make_desc(w + 512, 20480, 256, 3), 1);
            }
            wg_commit();
            if (tid == 0) TSTAMP(31 + gi);
            if (gi == 1 || gi == 2) {
                wg_wait<1>();
                const int bb = gi - 1;
#pragma unroll
                for (int c = 0; c < 4; c++) { X[bb][c] = ldg128_cg(px + CH(4 * (gi + 2) + c)); Y[bb][c] = ldg128_cg(py + CH(4 * (gi + 2) + c)); }
            }
        }
    }
    const uint32_t g0 = __ldcg(reinterpret_cast<const unsigned short*>(g_gate) + 128 * rb + 64 * wg + 16 * w4 + g);
    const uint32_t g1 = __ldcg(reinterpret_cast<const unsigned short*>(g_gate) + 128 * rb + 64 * wg + 16 * w4 + g + 8);
    wg_wait<0>();
    if (tid == 0) TSTAMP(6);
    mbar_wait(misc + B_AT, 0);
    if (tid == 0) TSTAMP(7);
    {
        const uint32_t gg[2] = {g0 | (g0 << 16), g1 | (g1 << 16)};
        const uint32_t om[2] = {hsub2_rn(0x3F803F80u, gg[0]), hsub2_rn(0x3F803F80u, gg[1])};
        const int m = lane >> 3, r = lane & 7;
        const int row = 64 * wg + 16 * w4 + r + 8 * (m & 1);
#pragma unroll
        for (int cg = 0; cg < 5; cg++) {
            uint32_t a[4];
            const int ch = 16 * cg + 8 * (m >> 1) + r;
            ldsm_x4_t(sb + OFF_AT + wg * 10240 + ch * 128 + (((2 * w4 + (m & 1)) ^ (ch & 7)) << 4), a[0], a[1], a[2], a[3]);
            uint32_t o[4];
#pragma unroll
            for (int q = 0; q < 4; q++) {
                const int j = 2 * cg + (q >> 1), hh = q & 1;
                const uint32_t b2 = pack_bf16(fa[4 * j + 2 * hh], fa[4 * j + 2 * hh + 1]);
                o[q] = hadd2_rn(hmul2_rn(gg[hh], a[q]), hmul2_rn(om[hh], b2));
            }
            stsm_x4(sb + OFF_OST + row * 160 + cg * 32 + (m >> 1) * 16, o[0], o[1], o[2], o[3]);
        }
    }
    fence_async();
    bar_sync(3 + wg, 128);
    if ((tid & 127) == 0) {
        tma_store2d(mOut, sb + OFF_OST + wg * 64 * 160, 80 * hg, 128 * rb + 64 * wg);
        bulk_commit();
        bulk_wait0();
        if (tid == 0) TSTAMP(8);
    }
}

__device__ __forceinline__ void load_a_tile(const CUtensorMap* mAT, uint32_t sb, int rb, int hg, unsigned ep) {
    const uint32_t misc = sb + OFF_MISC;
    mbar_wait(misc + B_CONV, 0);
    wait_counter(&g_cnt[(2 * 16 + hg) * 32], (ep + 1) * 32);
    fence_async_global();
    mbar_expect_tx(misc + B_AT, 20480);
    tma2d(sb + OFF_AT, mAT, rb * 128, hg * 80, misc + B_AT);
    tma2d(sb + OFF_AT + 10240, mAT, rb * 128 + 64, hg * 80, misc + B_AT);
}
__device__ __forceinline__ float bf_ld(const __nv_bfloat16* p) { return __uint_as_float((uint32_t)__ldg(reinterpret_cast<const unsigned short*>(p)) << 16); }
struct cpx { float x, y; };
__device__ __forceinline__ cpx cmul(cpx a, cpx b) { cpx r; r.x = fmaf(a.x, b.x, -a.y * b.y); r.y = fmaf(a.x, b.y, a.y * b.x); return r; }
__device__ __forceinline__ cpx csqr(cpx a) { cpx r; r.x = fmaf(a.x, a.x, -a.y * a.y); r.y = (a.x + a.x) * a.y; return r; }
__device__ __forceinline__ cpx cexp_v(float ar2, float ai, float v) {
    const float m = ex2f(ar2 * v), ph = ai * v;
    cpx r; r.x = m * __cosf(ph); r.y = m * __sinf(ph); return r;
}
__device__ __forceinline__ uint32_t pk_a(cpx a) { return pack_bf16(a.x, a.y); }
__device__ __forceinline__ uint32_t pk_b(cpx a) { return pack_bf16(a.x, -a.y); }

__device__ __forceinline__ void aux_gate(const Params& P, uint32_t sb, int rb, int hg, unsigned ep, int w4, int lane) {
    const int row = 128 * rb + 16 * hg + 4 * w4;
    const uint2* gw = reinterpret_cast<const uint2*>(P.gate_w);
    uint2 wv[5];
#pragma unroll
    for (int i = 0; i < 5; i++) wv[i] = __ldg(gw + lane + 32 * i);
    float s[4];
#pragma unroll
    for (int r = 0; r < 4; r++) {
        const uint2* x0 = reinterpret_cast<const uint2*>(P.u + (size_t)(row + r) * DM);
        s[r] = 0.f;
#pragma unroll
        for (int i = 0; i < 5; i++) {
            const uint2 a = __ldg(x0 + lane + 32 * i);
            const uint32_t p = hmul2_rn(a.x, wv[i].x), q = hmul2_rn(a.y, wv[i].y);
            s[r] += (bf_lo(p) + bf_hi(p)) + (bf_lo(q) + bf_hi(q));
        }
    }
#pragma unroll
    for (int o = 16; o > 0; o >>= 1)
#pragma unroll
        for (int r = 0; r < 4; r++) s[r] += __shfl_xor_sync(0xffffffffu, s[r], o);
    if (lane == 0) {
        uint32_t o[2];
#pragma unroll
        for (int r = 0; r < 2; r++) {
            const uint32_t sr = pack_bf16(s[2 * r], s[2 * r + 1]);
            o[r] = pack_bf16(1.f / (1.f + __expf(-bf_lo(sr))), 1.f / (1.f + __expf(-bf_hi(sr))));
        }
        *reinterpret_cast<uint2*>(g_gate + row) = make_uint2(o[0], o[1]);
        mbar_arrive(sb + OFF_MISC + B_GATE);
    }
    if (w4 == 0 && lane < 28) reinterpret_cast<float4*>(g_kvacc + (((ep + 1) & 1) * 8 + hg) * KV_STRIDE + rb * 112)[lane] = make_float4(0.f, 0.f, 0.f, 0.f);
}

__device__ __forceinline__ void aux_build_ut(const Params& P, uint32_t sb, int ch0, int t128) {
#pragma unroll
    for (int it = 0; it < 3; it++) {
        const int c = t128 + 128 * it;
        if (c < 320) sts128(sb + OFF_UT + (c >> 3) * UT_PLANE + (32 + (c & 7)) * 16, 0u, 0u, 0u, 0u);
    }
    const int boff = (ch0 * 2) & 7, sh = (boff & 3) * 8;
    const uint8_t* base = reinterpret_cast<const uint8_t*>(P.u) + ((ch0 * 2) & ~7);
#pragma unroll 4
    for (int it = 0; it < 8; it++) {
        const int l = 2 * (t128 + 128 * it);
        const uint2* p0 = reinterpret_cast<const uint2*>(base + (size_t)l * (DM * 2));
        const uint2* p1 = reinterpret_cast<const uint2*>(base + (size_t)(l + 1) * (DM * 2));
        const uint2 a0 = __ldg(p0), a1 = __ldg(p0 + 1), b0 = __ldg(p1), b1 = __ldg(p1 + 1);
        uint32_t x[3], y[3];
        if (boff < 4) { x[0] = __funnelshift_r(a0.x, a0.y, sh); x[1] = __funnelshift_r(a0.y, a1.x, sh); x[2] = __funnelshift_r(a1.x, a1.y, sh);
                        y[0] = __funnelshift_r(b0.x, b0.y, sh); y[1] = __funnelshift_r(b0.y, b1.x, sh); y[2] = __funnelshift_r(b1.x, b1.y, sh); }
        else          { x[0] = __funnelshift_r(a0.y, a1.x, sh); x[1] = __funnelshift_r(a1.x, a1.y, sh); x[2] = __funnelshift_r(a1.y, 0u, sh);
                        y[0] = __funnelshift_r(b0.y, b1.x, sh); y[1] = __funnelshift_r(b1.x, b1.y, sh); y[2] = __funnelshift_r(b1.y, 0u, sh); }
        const uint32_t dst = sb + OFF_UT + ((l >> 3) & 7) * UT_PLANE + (31 - (l >> 6)) * 16 + (l & 7) * 2;
        sts32(dst + 0 * UT_BYTES, __byte_perm(x[0], y[0], 0x5410));
        sts32(dst + 1 * UT_BYTES, __byte_perm(x[0], y[0], 0x7632));
        sts32(dst + 2 * UT_BYTES, __byte_perm(x[1], y[1], 0x5410));
        sts32(dst + 3 * UT_BYTES, __byte_perm(x[1], y[1], 0x7632));
        sts32(dst + 4 * UT_BYTES, __byte_perm(x[2], y[2], 0x5410));
    }
}

__device__ __forceinline__ float aux_kgen(const Params& P, uint32_t cst, int ch, int ks0, int ngroups, float (&acc)[5][4], int lane) {
    const int g = lane >> 2, t = lane & 3;
    const float dt = bf_lo(pack_bf16(expf(bf_ld(P.log_dt + ch)), 0.f));
    float k0 = 0.f;
    const float gf = (float)g;
#pragma unroll 1
    for (int gi = 0; gi < ngroups; gi++) {
        {
            const int s = lane >> 1, hf = lane & 1, idx = ch * 128 + ks0 * 8 + gi * 16 + s;
            const float ar2 = dt * bf_ld(P.A_re + idx) * 1.4426950408889634f, ai = dt * bf_ld(P.A_im + idx);
            cpx db, cc; db.x = dt * bf_ld(P.B_re + idx); db.y = dt * bf_ld(P.B_im + idx); cc.x = bf_ld(P.C_re + idx); cc.y = bf_ld(P.C_im + idx);
            const cpx c = cmul(cc, db);
            const cpx wv = cexp_v(ar2, ai, hf ? 128.f : 64.f);
            const cpx e1 = cmul(c, cexp_v(ar2, ai, hf ? 516.f : 1.f));
            const cpx e2 = cmul(c, cexp_v(ar2, ai, hf ? 1032.f : 258.f));
            __syncwarp();
            const uint32_t a = cst + s * 64;
            if (hf == 0) { sts128f(a, ar2, ai, wv.x, wv.y); sts64f(a + 16, e1.x, e1.y); sts64f(a + 32, e2.x, e2.y); k0 += c.x; }
            else { sts64f(a + 24, wv.x, wv.y); sts64f(a + 40, e1.x, e1.y); sts64f(a + 48, e2.x, e2.y); }
            __syncwarp();
        }
#pragma unroll 1
        for (int kk = 0; kk < 2; kk++) {
            uint32_t fa[4][4], fb[5][2];
#pragma unroll
            for (int h = 0; h < 2; h++) {
                const uint32_t a = cst + (kk * 8 + h * 4 + t) * 64;
                const float4 c0 = lds128f(a), c1 = lds128f(a + 16), c2 = lds128f(a + 32), c3 = lds128f(a + 48);
                const cpx x = cexp_v(c0.x, c0.y, gf);
                const cpx x2 = csqr(x), x4 = csqr(x2);
                cpx y = csqr(x4), z = cmul(y, cpx{c0.z, c0.w});
                const cpx b0 = cmul(cpx{c1.x, c1.y}, x);
                fb[0][h] = pk_b(b0);
                fb[1][h] = pk_b(cmul(b0, cpx{c1.z, c1.w}));
                fb[2][h] = pk_b(cmul(cpx{c2.x, c2.y}, x2));
                fb[3][h] = pk_b(cmul(cpx{c2.z, c2.w}, x4));
                fb[4][h] = pk_b(cmul(cpx{c3.x, c3.y}, y));
#pragma unroll
                for (int q = 0; q < 4; q++) {
                    fa[q][2 * h] = pk_a(y); fa[q][2 * h + 1] = pk_a(z);
                    if (q < 3) { y = csqr(y); z = csqr(z); }
                }
            }
            mma16816(acc[0], fa[0][0], fa[0][1], fa[0][2], fa[0][3], fb[0][0], fb[0][1]);
            mma16816(acc[1], fa[0][0], fa[0][1], fa[0][2], fa[0][3], fb[1][0], fb[1][1]);
            mma16816(acc[2], fa[1][0], fa[1][1], fa[1][2], fa[1][3], fb[2][0], fb[2][1]);
            mma16816(acc[3], fa[2][0], fa[2][1], fa[2][2], fa[2][3], fb[3][0], fb[3][1]);
            mma16816(acc[4], fa[3][0], fa[3][1], fa[3][2], fa[3][3], fb[4][0], fb[4][1]);
        }
    }
#pragma unroll
    for (int o = 16; o > 0; o >>= 1) k0 += __shfl_xor_sync(0xffffffffu, k0, o);
    return k0;
}

__device__ __forceinline__ void aux_phase1(const Params& P, uint32_t sb, int rb, int hg, unsigned ep, int w, int lane) {
    const int ch0 = 80 * hg + 5 * rb;
    const int g = lane >> 2, t = lane & 3;
    float acc[5][4];
#pragma unroll
    for (int i = 0; i < 5; i++) { acc[i][0] = 0.f; acc[i][1] = 0.f; acc[i][2] = 0.f; acc[i][3] = 0.f; }
    const uint32_t cst = sb + OFF_CST + w * 1024;
    int chs = w;
    float k0;
    bool fin = true;
    if (w < 4) {
        k0 = aux_kgen(P, cst, ch0 + w, 0, 8, acc, lane);
    } else {
        aux_gate(P, sb, rb, hg, ep, w - 4, lane);
        aux_build_ut(P, sb, ch0, threadIdx.x - 384);
        k0 = aux_kgen(P, cst, ch0 + 4, 4 * (w - 4), 2, acc, lane);
        chs = 4; fin = (w == 7);
#pragma unroll 1
        for (int s = 0; s < 4; s++) {
            if (w - 4 == s) {
#pragma unroll
                for (int i = 0; i < 5; i++) {
                    const uint32_t a = sb + OFF_K4 + (2 + 128 * i + 8 * g + 2 * t) * 4;
                    if (s > 0) { const uint2 p = lds64(a), q = lds64(a + 256);
                                 acc[i][0] += __uint_as_float(p.x); acc[i][1] += __uint_as_float(p.y); acc[i][2] += __uint_as_float(q.x); acc[i][3] += __uint_as_float(q.y); }
                    if (s < 3) { sts64f(a, acc[i][0], acc[i][1]); sts64f(a + 256, acc[i][2], acc[i][3]); }
                }
                if (lane == 0) { if (s > 0) k0 += lds32f(sb + OFF_K4); if (s < 3) sts32f(sb + OFF_K4, k0); }
            }
            if (s < 3) bar_sync(5, 128);
        }
    }
    if (fin) {
        const uint32_t kb = sb + OFF_KB + chs * KB_BYTES;
#pragma unroll
        for (int i = 0; i < 5; i++) {
            const uint32_t a = kb + (2 + 128 * i + 8 * g + 2 * t) * 2;
            sts32(a, pack_bf16(acc[i][0], acc[i][1])); sts32(a + 128, pack_bf16(acc[i][2], acc[i][3]));
        }
        if (lane == 0) sts32(kb, pack_bf16(0.f, k0));
    }
}

__device__ __forceinline__ uint32_t lds16(uint32_t addr) { uint16_t v; asm volatile("ld.shared.u16 %0, [%1];" : "=h"(v) : "r"(addr) : "memory"); return v; }
__device__ __forceinline__ void aux_tables(uint32_t sb, int t256) {
    if (t256 < 80) sts128(sb + OFF_TAB + (t256 >> 4) * TAB_BYTES + (t256 & 15) * 16, 0u, 0u, 0u, 0u);
#pragma unroll
    for (int it = 0; it < 2; it++) {
        const int p = 4 * (t256 + 256 * it);
        uint32_t pos[5];
#pragma unroll
        for (int x = 0; x < 5; x++) {
            const int j = p - 1 + x;
            const uint32_t b = pack_bf16((float)j, 0.f) & 0xFFFFu;
            pos[x] = 2 * (j < 128 ? j + 1 : (int)b - 17023);
        }
#pragma unroll
        for (int ch = 0; ch < 5; ch++) {
            uint32_t k[5];
#pragma unroll
            for (int x = 0; x < 5; x++) k[x] = lds16(sb + OFF_KB + ch * KB_BYTES + pos[x]);
            sts128(sb + OFF_TAB + ch * TAB_BYTES + (p + 64) * 4, k[1] | (k[0] << 16), k[2] | (k[1] << 16), k[3] | (k[2] << 16), k[4] | (k[3] << 16));
        }
    }
}

template <int C> __device__ __forceinline__ void conv_mma(float (&acc)[16], const uint32_t (&a)[4], uint64_t desc) {
    if constexpr (C == 0) wgmma_n32_rs_ta0_tb0(acc, a[0], a[1], a[2], a[3], desc, 1);
    else if constexpr (C == 1) wgmma_n24_rs_ta0_tb0(*reinterpret_cast<float(*)[12]>(&acc[0]), a[0], a[1], a[2], a[3], desc, 1);
    else if constexpr (C == 2) wgmma_n16_rs_ta0_tb0(*reinterpret_cast<float(*)[8]>(&acc[0]), a[0], a[1], a[2], a[3], desc, 1);
    else wgmma_n8_rs_ta0_tb0(*reinterpret_cast<float(*)[4]>(&acc[0]), a[0], a[1], a[2], a[3], desc, 1);
}
__device__ __forceinline__ void conv_load(uint32_t (&Q)[4][4], uint32_t addr) {
#pragma unroll
    for (int ks = 0; ks < 4; ks++) { Q[ks][0] = lds32(addr + 32 * (7 - 2 * ks)); Q[ks][1] = lds32(addr + 32 * (8 - 2 * ks)); }
    Q[3][2] = lds32(addr);
#pragma unroll
    for (int ks = 0; ks < 4; ks++) {
        asm volatile("mov.b32 %0, %1;" : "=r"(Q[ks][3]) : "r"(Q[ks][0]));
        if (ks < 3) asm volatile("mov.b32 %0, %1;" : "=r"(Q[ks][2]) : "r"(Q[ks + 1][1]));
    }
}
template <int C> __device__ __forceinline__ void conv_block(float (&acc)[16], uint32_t rbase, uint32_t dlo) {
    uint32_t Q[2][4][4];
    const uint32_t rb = rbase + C * 8 * 256;
    conv_load(Q[0], rb);
#pragma unroll
    for (int i = 0; i < 8; i++) {
        wg_fence();
#pragma unroll
        for (int ks = 0; ks < 4; ks++) {
            const uint32_t lo = dlo + (2 * ks * UT_PLANE >> 4) + 8 * C + i;
            const uint64_t desc = (uint64_t)lo | ((uint64_t)(128 >> 4) << 32);
            conv_mma<C>(acc, Q[i & 1][ks], desc);
        }
        wg_commit();
        if (i < 7) {
            wg_wait<1>();
            conv_load(Q[(i + 1) & 1], rb + (i + 1) * 256);
        }
    }
    wg_wait<0>();
}
__device__ __forceinline__ void conv_channel(float (&acc)[16], uint32_t sb, int c, int mask, int w4, int lane) {
    const int g = lane >> 2, t = lane & 3;
    const uint32_t rbase = sb + OFF_TAB + c * TAB_BYTES + (8 + 16 * w4 + g - 2 * t) * 4;
    const uint32_t dlo = (((sb + OFF_UT + c * UT_BYTES) & 0x3FFFF) >> 4) | ((UT_PLANE >> 4) << 16);
#pragma unroll
    for (int i = 0; i < 16; i++) acc[i] = 0.f;
    if (mask & 1) conv_block<0>(acc, rbase, dlo);
    if (mask & 2) conv_block<1>(acc, rbase, dlo);
    if (mask & 4) conv_block<2>(acc, rbase, dlo);
    if (mask & 8) conv_block<3>(acc, rbase, dlo);
}
__device__ __forceinline__ void conv_store(const Params& P, const float (&acc)[16], uint32_t sb, int c, int chg, int barid, int w4, int lane, int t128) {
    const uint32_t d1 = (uint32_t)__ldg(reinterpret_cast<const unsigned short*>(P.Dskip) + chg), d2 = d1 | (d1 << 16);
    const uint32_t ut = sb + OFF_UT + c * UT_BYTES;
    bar_sync(barid, 128);
    const int mi = lane >> 3;
#pragma unroll
    for (int jj = 0; jj < 2; jj++) {
        const uint32_t a = ut + (2 * w4 + (mi & 1)) * UT_PLANE + (16 * jj + 8 * (mi >> 1) + (lane & 7)) * 16;
        uint32_t u[4], o[4];
        ldsm_x4_t(a, u[0], u[1], u[2], u[3]);
#pragma unroll
        for (int q = 0; q < 4; q++) {
            const int r = 8 * jj + 4 * (q >> 1) + 2 * (q & 1);
            o[q] = hadd2_rn(pack_bf16(acc[r], acc[r + 1]), hmul2_rn(u[q], d2));
        }
        stsm_x4_t(a, o[0], o[1], o[2], o[3]);
    }
    bar_sync(barid, 128);
#pragma unroll
    for (int it = 0; it < 2; it++) {
        const int q = t128 + 128 * it;
        stg128(g_aT + (size_t)chg * SEQ + 8 * q, lds128(ut + (q & 7) * UT_PLANE + (31 - (q >> 3)) * 16));
    }
}
__device__ __forceinline__ void aux_role(const Params& P, const CUtensorMap* mAT, uint32_t sb, int rb, int hg, unsigned ep) {
    const int lane = threadIdx.x & 31, w = (threadIdx.x >> 5) - 8, wgi = w >> 2, w4 = w & 3, t128 = threadIdx.x & 127;
    const int ch0 = 80 * hg + 5 * rb;
    aux_phase1(P, sb, rb, hg, ep, w, lane);
    if (lane == 0 && (w == 0 || w == 4)) TSTAMP(40 + (w >> 2));
    bar_sync(2, 256);
    mbar_wait(sb + OFF_MISC + B_TABFREE, 0);
    if (threadIdx.x == 256) TSTAMP(42);
    aux_tables(sb, threadIdx.x - 256);
    bar_sync(2, 256);
    if (threadIdx.x == 256) TSTAMP(43);
    float acc[16];
#pragma unroll 1
    for (int it = 0; it < 3; it++) {
        const int c = it < 2 ? 2 * wgi + it : 4;
        conv_channel(acc, sb, c, it < 2 ? 15 : (wgi == 0 ? 9 : 6), w4, lane);
        if (t128 == 0) TSTAMP(44 + 4 * wgi + it);
        if (it == 2) {
            const uint32_t xb = sb + OFF_TAB + 2 * TAB_BYTES + t128 * 16;
            if (wgi == 1) {
#pragma unroll
                for (int q = 0; q < 4; q++) sts128f(xb + q * 2048, acc[4 * q], acc[4 * q + 1], acc[4 * q + 2], acc[4 * q + 3]);
            }
            bar_sync(2, 256);
            if (wgi == 1) break;
#pragma unroll
            for (int q = 0; q < 4; q++) { const float4 v = lds128f(xb + q * 2048); acc[4 * q] += v.x; acc[4 * q + 1] += v.y; acc[4 * q + 2] += v.z; acc[4 * q + 3] += v.w; }
        }
        conv_store(P, acc, sb, c, ch0 + c, 6 + wgi, w4, lane, t128);
    }
    bar_sync(6 + wgi, 128);
    if (t128 == 0) {
        TSTAMP(47 + 4 * wgi);
        mbar_arrive(sb + OFF_MISC + B_CONV);
        red_release(&g_cnt[(2 * 16 + hg) * 32], 1u);
        if (wgi == 0) load_a_tile(mAT, sb, rb, hg, ep);
    }
}
__global__ void __launch_bounds__(NTHREADS, 1)
fused_kernel(const __grid_constant__ CUtensorMap mA, const __grid_constant__ CUtensorMap mB0, const __grid_constant__ CUtensorMap mB1,
             const __grid_constant__ CUtensorMap mWo, const __grid_constant__ CUtensorMap mOut,
             const __grid_constant__ CUtensorMap mAT, const __grid_constant__ Params P) {
    extern __shared__ __align__(1024) uint8_t smem_raw[];
    const uint32_t sb = smem_u32(smem_raw);
    const int tid = threadIdx.x, warp = tid >> 5;
    const int g16 = blockIdx.x >> 4, i16 = blockIdx.x & 15;
    const int rb = (g16 & 3) * 4 + (i16 & 1) + ((i16 >> 2) & 1) * 2;
    const int hg = (g16 >> 2) * 4 + ((i16 >> 1) & 1) + (i16 >> 3) * 2;
    const uint32_t misc = sb + OFF_MISC;
    if (tid == 0) {
        TSTAMP(0);
        for (int s = 0; s < 4; s++) { mbar_init(misc + B_FULL + 8 * s, 1); sts32(misc + M_STG + 4 * s, 0); }
        mbar_init(misc + B_WO, 1); mbar_init(misc + B_TABFREE, 2); mbar_init(misc + B_GATE, 4); mbar_init(misc + B_AT, 1);
        mbar_init(misc + B_CONV, 2);
        asm volatile("fence.mbarrier_init.release.cluster;" ::: "memory");
        for (int kb = 0; kb < 4; kb++) issue_stage(&mA, &mB0, &mB1, sb, kb, rb, hg);
    }
    if (tid == 32) sts32(misc + M_EPOCH, ld_relaxed(&g_cnt[(0 * 16 + hg) * 32]) >> 4);
    __syncthreads();
    const unsigned ep = lds32(misc + M_EPOCH);
    if (warp < 8) {
        asm volatile("setmaxnreg.inc.sync.aligned.u32 168;");
        consumer_role(P, &mA, &mB0, &mB1, &mWo, &mOut, sb, rb, hg, ep);
    } else {
        asm volatile("setmaxnreg.dec.sync.aligned.u32 88;");
        aux_role(P, &mAT, sb, rb, hg, ep);
    }
}

typedef CUresult (*PFN_encodeTiled)(CUtensorMap*, CUtensorMapDataType, cuuint32_t, void*, const cuuint64_t*, const cuuint64_t*, const cuuint32_t*,
                                    const cuuint32_t*, CUtensorMapInterleave, CUtensorMapSwizzle, CUtensorMapL2promotion, CUtensorMapFloatOOBfill);
CUtensorMap make_map(PFN_encodeTiled enc, const void* base, int rank, const cuuint64_t* dims, const cuuint64_t* strides, const cuuint32_t* box, CUtensorMapSwizzle sw) {
    CUtensorMap m; const cuuint32_t es[5] = {1, 1, 1, 1, 1};
    enc(&m, CU_TENSOR_MAP_DATA_TYPE_BFLOAT16, rank, const_cast<void*>(base), dims, strides, box, es, CU_TENSOR_MAP_INTERLEAVE_NONE, sw,
        CU_TENSOR_MAP_L2_PROMOTION_L2_128B, CU_TENSOR_MAP_FLOAT_OOB_FILL_NONE);
    return m;
}
long long* g_dbg_tim = nullptr;

}

extern "C" void kernel_launch(void* const* d_in, const int* in_sizes, int n_in, void* d_out, int out_size) {
    (void)in_sizes; (void)n_in; (void)out_size;
    static PFN_encodeTiled enc = nullptr;
    static void *p_o = nullptr, *p_aT = nullptr;
    if (!enc) {
        void* fn = nullptr; cudaDriverEntryPointQueryResult qr;
        cudaGetDriverEntryPoint("cuTensorMapEncodeTiled", &fn, cudaEnableDefault, &qr);
        enc = (PFN_encodeTiled)fn;
        cudaGetSymbolAddress(&p_o, g_o); cudaGetSymbolAddress(&p_aT, g_aT);
        cudaFuncSetAttribute(fused_kernel, cudaFuncAttributeMaxDynamicSharedMemorySize, SMEM_BYTES);
    }
    CUtensorMap mA, mB0, mB1, mWo, mOut, mAT;
    { const cuuint64_t d[2] = {640, 2048}, st[1] = {1280}; const cuuint32_t b[2] = {64, 128}; mA = make_map(enc, d_in[0], 2, d, st, b, CU_TENSOR_MAP_SWIZZLE_128B); }
    { const cuuint64_t d[3] = {640, 640, 3}, st[2] = {3840, 1280}; const cuuint32_t b[3] = {64, 64, 3}, b1[3] = {16, 64, 3};
      mB0 = make_map(enc, d_in[10], 3, d, st, b, CU_TENSOR_MAP_SWIZZLE_128B); mB1 = make_map(enc, d_in[10], 3, d, st, b1, CU_TENSOR_MAP_SWIZZLE_32B); }
    { const cuuint64_t d[5] = {640, 2, 4, 4, 20}, st[4] = {1280, 10240, 2560, 40960}; const cuuint32_t b[5] = {16, 2, 4, 4, 20};
      mWo = make_map(enc, d_in[11], 5, d, st, b, CU_TENSOR_MAP_SWIZZLE_32B); }
    { const cuuint64_t d[2] = {640, 2048}, st[1] = {1280}; const cuuint32_t b[2] = {80, 64};
      mOut = make_map(enc, d_out, 2, d, st, b, CU_TENSOR_MAP_SWIZZLE_NONE); }
    { const cuuint64_t d[2] = {2048, 640}, st[1] = {4096}; const cuuint32_t b[2] = {64, 80}; mAT = make_map(enc, p_aT, 2, d, st, b, CU_TENSOR_MAP_SWIZZLE_128B); }
    Params P;
    P.u = (const __nv_bfloat16*)d_in[0]; P.A_re = (const __nv_bfloat16*)d_in[1]; P.A_im = (const __nv_bfloat16*)d_in[2];
    P.B_re = (const __nv_bfloat16*)d_in[3]; P.B_im = (const __nv_bfloat16*)d_in[4]; P.C_re = (const __nv_bfloat16*)d_in[5];
    P.C_im = (const __nv_bfloat16*)d_in[6]; P.log_dt = (const __nv_bfloat16*)d_in[7]; P.Dskip = (const __nv_bfloat16*)d_in[8];
    P.gate_w = (const __nv_bfloat16*)d_in[12]; P.tim = g_dbg_tim;
    fused_kernel<<<128, NTHREADS, SMEM_BYTES, cudaStreamPerThread>>>(mA, mB0, mB1, mWo, mOut, mAT, P);
}
```

```cpp
#include <cuda_runtime.h>
#include <cuda_bf16.h>
#include <cuda.h>
#include <stdint.h>

namespace {

constexpr int SEQ = 2048, DM = 640;
constexpr int NTHREADS = 512;
constexpr int ST_BYTES = 47104;
constexpr int NST = 3;
constexpr int OFF_PK = 0, OFF_V = 20480, OFF_ONES = 40960;
constexpr int OFF_WO = 38912;
constexpr int OFF_KVB = 0;
constexpr int OFF_KVST = 45056;
constexpr int OFF_OST = 18432;
constexpr int OFF_TAB = 141312;
constexpr int TAB_BYTES = 8448;
constexpr int OFF_AT = 141312;
constexpr int OFF_UT = 188416;
constexpr int UT_PLANE = 1184, UT_BYTES = 4 * UT_PLANE;
constexpr int OFF_KB = OFF_UT + 5 * UT_BYTES;
constexpr int KB_BYTES = 1296;
constexpr int OFF_KS = OFF_TAB;
constexpr int KS_PITCH = 720, KS_CST = 23168, KS_BYTES = KS_CST + 4096;
constexpr int OFF_KX = OFF_KB + 5 * KB_BYTES;
constexpr int OFF_PS = 221696;
constexpr int OFF_X = OFF_KB;
constexpr int X_BYTES = 64 * 36 * 4;
constexpr int OFF_MISC = 231936;
constexpr int SMEM_BYTES = OFF_MISC + 512;
static_assert(OFF_KX + 3072 <= OFF_PS && OFF_PS + 7680 <= OFF_MISC && OFF_KS + 2 * KS_BYTES <= OFF_KB && OFF_KX + 3072 <= OFF_MISC && OFF_X + 2 * X_BYTES <= OFF_MISC && KS_BYTES % 128 == 0, "smem map");
constexpr int B_FULL = 0, B_WO = 64, B_GATE = 80, B_AT = 88, B_CONV = 96, B_U0 = 104, B_UT = 112, B_OF = 192;
constexpr int M_EPOCH = 160, M_EPOCH1 = 164, M_STG = 176, M_OSTG = 232;
__host__ __device__ constexpr int oslot_off(int s) { return s < 2 ? s * 16384 : OFF_WO + 51200 - 32768 + s * 16384; }
static_assert(oslot_off(4) + 16384 <= NST * ST_BYTES, "smem map");
constexpr int SPIN_LIMIT = 1 << 18;

constexpr int KV_STRIDE = 1792;
__device__ float g_kvacc[2 * 8 * KV_STRIDE];
__device__ unsigned g_cnt[4 * 16 * 32];
__device__ __nv_bfloat16 g_uT[DM * SEQ];
__device__ __nv_bfloat16 g_gate[SEQ];
__device__ __nv_bfloat16 g_o[SEQ * DM];
__device__ __nv_bfloat16 g_aT[DM * SEQ];

__device__ __forceinline__ uint32_t smem_u32(const void* p) { return (uint32_t)__cvta_generic_to_shared(p); }
__device__ __forceinline__ void mbar_init(uint32_t bar, int cnt) { asm volatile("mbarrier.init.shared::cta.b64 [%0], %1;" :: "r"(bar), "r"(cnt)); }
__device__ __forceinline__ void mbar_expect_tx(uint32_t bar, uint32_t bytes) { asm volatile("mbarrier.arrive.expect_tx.shared::cta.b64 _, [%0], %1;" :: "r"(bar), "r"(bytes) : "memory"); }
__device__ __forceinline__ void mbar_arrive(uint32_t bar) { asm volatile("mbarrier.arrive.shared::cta.b64 _, [%0];" :: "r"(bar) : "memory"); }
#define MBAR_HINT 20000
__device__ __forceinline__ bool mbar_try(uint32_t bar, uint32_t parity) {
    uint32_t ok;
    asm volatile("{\n.reg .pred p;\nmbarrier.try_wait.parity.shared::cta.b64 p, [%1], %2, %3;\nselp.u32 %0, 1, 0, p;\n}" : "=r"(ok) : "r"(bar), "r"(parity), "n"(MBAR_HINT) : "memory");
    return ok;
}
__device__ __forceinline__ void mbar_wait(uint32_t bar, uint32_t parity) {
#pragma unroll 1
    for (int i = 0; i < SPIN_LIMIT; i++) { if (mbar_try(bar, parity)) return; }
    __trap();
}
__device__ __forceinline__ void tma2d(uint32_t dst, const CUtensorMap* m, int c0, int c1, uint32_t bar) {
    asm volatile("cp.async.bulk.tensor.2d.shared::cluster.global.mbarrier::complete_tx::bytes [%0], [%1, {%3, %4}], [%2];" :: "r"(dst), "l"(m), "r"(bar), "r"(c0), "r"(c1) : "memory");
}
__device__ __forceinline__ void tma3d(uint32_t dst, const CUtensorMap* m, int c0, int c1, int c2, uint32_t bar) {
    asm volatile("cp.async.bulk.tensor.3d.shared::cluster.global.mbarrier::complete_tx::bytes [%0], [%1, {%3, %4, %5}], [%2];" :: "r"(dst), "l"(m), "r"(bar), "r"(c0), "r"(c1), "r"(c2) : "memory");
}
__device__ __forceinline__ void tma5d(uint32_t dst, const CUtensorMap* m, int c0, uint32_t bar) {
    asm volatile("cp.async.bulk.tensor.5d.shared::cluster.global.mbarrier::complete_tx::bytes [%0], [%1, {%3, %4, %4, %4, %4}], [%2];" :: "r"(dst), "l"(m), "r"(bar), "r"(c0), "r"(0) : "memory");
}
__device__ __forceinline__ void tma_store2d(const CUtensorMap* m, uint32_t src, int c0, int c1) {
    asm volatile("cp.async.bulk.tensor.2d.global.shared::cta.bulk_group [%0, {%2, %3}], [%1];" :: "l"(m), "r"(src), "r"(c0), "r"(c1) : "memory");
}
__device__ __forceinline__ void bulk_load(uint32_t dst, const void* src, uint32_t bytes, uint32_t bar) {
    asm volatile("cp.async.bulk.shared::cluster.global.mbarrier::complete_tx::bytes [%0], [%1], %2, [%3];" :: "r"(dst), "l"(src), "r"(bytes), "r"(bar) : "memory");
}
__device__ __forceinline__ void prefetch_map(const CUtensorMap* m) { asm volatile("prefetch.tensormap [%0];" :: "l"(m) : "memory"); }
__device__ __forceinline__ void prefetch_l2(const void* p, uint32_t bytes) { asm volatile("cp.async.bulk.prefetch.L2.global [%0], %1;" :: "l"(p), "r"(bytes) : "memory"); }
__device__ __forceinline__ void bulk_commit() { asm volatile("cp.async.bulk.commit_group;" ::: "memory"); }
__device__ __forceinline__ void bulk_wait0() { asm volatile("cp.async.bulk.wait_group 0;" ::: "memory"); }
__device__ __forceinline__ void fence_async() { asm volatile("fence.proxy.async.shared::cta;" ::: "memory"); }
__device__ __forceinline__ void fence_async_global() { asm volatile("fence.proxy.async.global;" ::: "memory"); }
__device__ __forceinline__ void wg_fence() { asm volatile("wgmma.fence.sync.aligned;" ::: "memory"); }
__device__ __forceinline__ void wg_commit() { asm volatile("wgmma.commit_group.sync.aligned;" ::: "memory"); }
template <int N> __device__ __forceinline__ void wg_wait() { asm volatile("wgmma.wait_group.sync.aligned %0;" :: "n"(N) : "memory"); }
__device__ __forceinline__ uint64_t make_desc(uint32_t addr, uint32_t lbo, uint32_t sbo, int swz) {
    return (uint64_t)((addr & 0x3FFFF) >> 4) | ((uint64_t)(lbo >> 4) << 16) | ((uint64_t)(sbo >> 4) << 32) | ((uint64_t)swz << 62);
}
__device__ __forceinline__ void bar_sync(int id, int n) { asm volatile("bar.sync %0, %1;" :: "r"(id), "r"(n) : "memory"); }
__device__ __forceinline__ void bar_arrive(int id, int n) { asm volatile("bar.arrive %0, %1;" :: "r"(id), "r"(n) : "memory"); }
__device__ __forceinline__ uint32_t lds32v(uint32_t addr) {
    uint32_t v; asm volatile("ld.volatile.shared.b32 %0, [%1];" : "=r"(v) : "r"(addr) : "memory"); return v;
}
__device__ __forceinline__ uint32_t pack_bf16(float lo, float hi) {
    uint32_t r; asm("cvt.rn.bf16x2.f32 %0, %1, %2;" : "=r"(r) : "f"(hi), "f"(lo)); return r;
}
__device__ __forceinline__ float bf_lo(uint32_t v) { return __uint_as_float(v << 16); }
__device__ __forceinline__ float bf_hi(uint32_t v) { return __uint_as_float(v & 0xFFFF0000u); }
__device__ __forceinline__ float ex2f(float x) { float r; asm("ex2.approx.ftz.f32 %0, %1;" : "=f"(r) : "f"(x)); return r; }
__device__ __forceinline__ uint32_t hmul2_rn(uint32_t a, uint32_t b) { uint32_t r; asm("mul.rn.bf16x2 %0, %1, %2;" : "=r"(r) : "r"(a), "r"(b)); return r; }
__device__ __forceinline__ uint32_t hadd2_rn(uint32_t a, uint32_t b) { uint32_t r; asm("add.rn.bf16x2 %0, %1, %2;" : "=r"(r) : "r"(a), "r"(b)); return r; }
__device__ __forceinline__ uint32_t hsub2_rn(uint32_t a, uint32_t b) { uint32_t r; asm("sub.rn.bf16x2 %0, %1, %2;" : "=r"(r) : "r"(a), "r"(b)); return r; }
__device__ __forceinline__ void stsm_x4(uint32_t addr, uint32_t r0, uint32_t r1, uint32_t r2, uint32_t r3) {
    asm volatile("stmatrix.sync.aligned.m8n8.x4.shared.b16 [%0], {%1, %2, %3, %4};" :: "r"(addr), "r"(r0), "r"(r1), "r"(r2), "r"(r3) : "memory");
}
__device__ __forceinline__ void stsm_x4_t(uint32_t addr, uint32_t r0, uint32_t r1, uint32_t r2, uint32_t r3) {
    asm volatile("stmatrix.sync.aligned.m8n8.x4.trans.shared.b16 [%0], {%1, %2, %3, %4};" :: "r"(addr), "r"(r0), "r"(r1), "r"(r2), "r"(r3) : "memory");
}
__device__ __forceinline__ void ldsm_x4_t(uint32_t addr, uint32_t& r0, uint32_t& r1, uint32_t& r2, uint32_t& r3) {
    asm volatile("ldmatrix.sync.aligned.m8n8.x4.trans.shared.b16 {%0, %1, %2, %3}, [%4];" : "=r"(r0), "=r"(r1), "=r"(r2), "=r"(r3) : "r"(addr) : "memory");
}
__device__ __forceinline__ void sts128(uint32_t addr, uint32_t a, uint32_t b, uint32_t c, uint32_t d) {
    asm volatile("st.shared.v4.b32 [%0], {%1, %2, %3, %4};" :: "r"(addr), "r"(a), "r"(b), "r"(c), "r"(d) : "memory");
}
__device__ __forceinline__ uint4 lds128(uint32_t addr) {
    uint4 v; asm volatile("ld.shared.v4.b32 {%0, %1, %2, %3}, [%4];" : "=r"(v.x), "=r"(v.y), "=r"(v.z), "=r"(v.w) : "r"(addr) : "memory"); return v;
}
__device__ __forceinline__ uint2 lds64(uint32_t addr) {
    uint2 v; asm volatile("ld.shared.v2.b32 {%0, %1}, [%2];" : "=r"(v.x), "=r"(v.y) : "r"(addr) : "memory"); return v;
}
__device__ __forceinline__ uint32_t lds32(uint32_t addr) {
    uint32_t v; asm volatile("ld.shared.b32 %0, [%1];" : "=r"(v) : "r"(addr) : "memory"); return v;
}
__device__ __forceinline__ void sts32(uint32_t addr, uint32_t v) { asm volatile("st.shared.b32 [%0], %1;" :: "r"(addr), "r"(v) : "memory"); }
__device__ __forceinline__ uint4 ldg128_cg(const void* p) {
    uint4 v; asm volatile("ld.global.cg.v4.b32 {%0, %1, %2, %3}, [%4];" : "=r"(v.x), "=r"(v.y), "=r"(v.z), "=r"(v.w) : "l"(p) : "memory"); return v;
}
__device__ __forceinline__ unsigned ld_acquire(const unsigned* p) {
    unsigned v; asm volatile("ld.acquire.gpu.global.u32 %0, [%1];" : "=r"(v) : "l"(p) : "memory"); return v;
}
__device__ __forceinline__ unsigned ld_relaxed(const unsigned* p) {
    unsigned v; asm volatile("ld.relaxed.gpu.global.u32 %0, [%1];" : "=r"(v) : "l"(p) : "memory"); return v;
}
__device__ __forceinline__ void red_release(unsigned* p, unsigned v) { asm volatile("red.release.gpu.global.add.u32 [%0], %1;" :: "l"(p), "r"(v) : "memory"); }
__device__ __forceinline__ void wait_counter(const unsigned* p, unsigned target) {
#pragma unroll 1
    for (int i = 0; i < SPIN_LIMIT; i++) { if ((int)(ld_acquire(p) - target) >= 0) return; }
    __trap();
}
__device__ __forceinline__ void red_add_v2(float* p, float a, float b) { asm volatile("red.global.add.v2.f32 [%0], {%1, %2};" :: "l"(p), "f"(a), "f"(b) : "memory"); }
__device__ __forceinline__ void red_add_f(float* p, float a) { asm volatile("red.global.add.f32 [%0], %1;" :: "l"(p), "f"(a) : "memory"); }
__device__ __forceinline__ void mma16816(float (&d)[4], uint32_t a0, uint32_t a1, uint32_t a2, uint32_t a3, uint32_t b0, uint32_t b1) {
    asm volatile("mma.sync.aligned.m16n8k16.row.col.f32.bf16.bf16.f32 {%0,%1,%2,%3}, {%4,%5,%6,%7}, {%8,%9}, {%0,%1,%2,%3};"
                 : "+f"(d[0]), "+f"(d[1]), "+f"(d[2]), "+f"(d[3]) : "r"(a0), "r"(a1), "r"(a2), "r"(a3), "r"(b0), "r"(b1));
}
__device__ __forceinline__ uint32_t atom_inc_cta(uint32_t addr) {
    uint32_t v; asm volatile("atom.acq_rel.cta.shared.add.u32 %0, [%1], 1;" : "=r"(v) : "r"(addr) : "memory"); return v;
}
__device__ __forceinline__ uint32_t phi2(float a, float b) {
    const uint32_t t2 = pack_bf16(a, b);
    const uint32_t e2 = pack_bf16(ex2f(bf_lo(t2) * 1.4426950408889634f), ex2f(bf_hi(t2) * 1.4426950408889634f));
    const uint32_t p2 = hadd2_rn(t2, 0x3F803F80u);
    uint32_t m; asm("set.gt.u32.bf16x2 %0, %1, %2;" : "=r"(m) : "r"(t2), "r"(0u));
    return hadd2_rn((p2 & m) | (e2 & ~m), 0x35863586u);
}
__device__ __forceinline__ float rcp_fast(float x) { float r; asm("rcp.approx.ftz.f32 %0, %1;" : "=f"(r) : "f"(x)); return r; }
__device__ __forceinline__ void sts64(uint32_t addr, uint32_t a, uint32_t b) { asm volatile("st.shared.v2.b32 [%0], {%1, %2};" :: "r"(addr), "r"(a), "r"(b) : "memory"); }
__device__ __forceinline__ void sts64f(uint32_t addr, float a, float b) { asm volatile("st.shared.v2.f32 [%0], {%1, %2};" :: "r"(addr), "f"(a), "f"(b) : "memory"); }
__device__ __forceinline__ void sts32f(uint32_t addr, float a) { asm volatile("st.shared.f32 [%0], %1;" :: "r"(addr), "f"(a) : "memory"); }
__device__ __forceinline__ void sts16(uint32_t addr, uint32_t v) { asm volatile("st.shared.b16 [%0], %1;" :: "r"(addr), "h"((unsigned short)v) : "memory"); }
__device__ __forceinline__ void bulk_reduce_add_f32(void* dst, uint32_t src, uint32_t bytes) {
    asm volatile("cp.reduce.async.bulk.global.shared::cta.bulk_group.add.f32 [%0], [%1], %2;" :: "l"(dst), "r"(src), "r"(bytes) : "memory");
}
__device__ __forceinline__ void ldsm_x4(uint32_t addr, uint32_t& r0, uint32_t& r1, uint32_t& r2, uint32_t& r3) {
    asm volatile("ldmatrix.sync.aligned.m8n8.x4.shared.b16 {%0, %1, %2, %3}, [%4];" : "=r"(r0), "=r"(r1), "=r"(r2), "=r"(r3) : "r"(addr) : "memory");
}
__device__ __forceinline__ void ldsm_x2(uint32_t addr, uint32_t& r0, uint32_t& r1) {
    asm volatile("ldmatrix.sync.aligned.m8n8.x2.shared.b16 {%0, %1}, [%2];" : "=r"(r0), "=r"(r1) : "r"(addr) : "memory");
}
__device__ __forceinline__ float4 lds128f(uint32_t addr) {
    float4 v; asm volatile("ld.shared.v4.f32 {%0, %1, %2, %3}, [%4];" : "=f"(v.x), "=f"(v.y), "=f"(v.z), "=f"(v.w) : "r"(addr) : "memory"); return v;
}
__device__ __forceinline__ float lds32f(uint32_t addr) { float v; asm volatile("ld.shared.f32 %0, [%1];" : "=f"(v) : "r"(addr) : "memory"); return v; }
__device__ __forceinline__ void sts128f(uint32_t addr, float a, float b, float c, float d) {
    asm volatile("st.shared.v4.f32 [%0], {%1, %2, %3, %4};" :: "r"(addr), "f"(a), "f"(b), "f"(c), "f"(d) : "memory");
}
__device__ __forceinline__ void stg128(void* p, uint4 v) { asm volatile("st.global.v4.b32 [%0], {%1, %2, %3, %4};" :: "l"(p), "r"(v.x), "r"(v.y), "r"(v.z), "r"(v.w) : "memory"); }
__device__ __forceinline__ void wgmma_n192_ss_ta0_tb1(float (&d)[96], uint64_t descA, uint64_t descB, int scaleD) {
  asm volatile("{\n.reg .pred p;\n"
    "setp.ne.b32 p, %98, 0;\n"
    "wgmma.mma_async.sync.aligned.m64n192k16.f32.bf16.bf16 "
    "{%0, %1, %2, %3, %4, %5, %6, %7, %8, %9, %10, %11, %12, %13, %14, %15, %16, %17, %18, %19, %20, %21, %22, %23, %24, %25, %26, %27, %28, %29, %30, %31, %32, %33, %34, %35, %36, %37, %38, %39, %40, %41, %42, %43, %44, %45, %46, %47, %48, %49, %50, %51, %52, %53, %54, %55, %56, %57, %58, %59, %60, %61, %62, %63, %64, %65, %66, %67, %68, %69, %70, %71, %72, %73, %74, %75, %76, %77, %78, %79, %80, %81, %82, %83, %84, %85, %86, %87, %88, %89, %90, %91, %92, %93, %94, %95}, "
    "%96, %97, p, 1, 1, 0, 1;\n}\n"
    : "+f"(d[0]), "+f"(d[1]), "+f"(d[2]), "+f"(d[3]), "+f"(d[4]), "+f"(d[5]), "+f"(d[6]), "+f"(d[7]), "+f"(d[8]), "+f"(d[9]), "+f"(d[10]), "+f"(d[11]), "+f"(d[12]), "+f"(d[13]), "+f"(d[14]), "+f"(d[15]), "+f"(d[16]), "+f"(d[17]), "+f"(d[18]), "+f"(d[19]), "+f"(d[20]), "+f"(d[21]), "+f"(d[22]), "+f"(d[23]), "+f"(d[24]), "+f"(d[25]), "+f"(d[26]), "+f"(d[27]), "+f"(d[28]), "+f"(d[29]), "+f"(d[30]), "+f"(d[31]), "+f"(d[32]), "+f"(d[33]), "+f"(d[34]), "+f"(d[35]), "+f"(d[36]), "+f"(d[37]), "+f"(d[38]), "+f"(d[39]), "+f"(d[40]), "+f"(d[41]), "+f"(d[42]), "+f"(d[43]), "+f"(d[44]), "+f"(d[45]), "+f"(d[46]), "+f"(d[47]), "+f"(d[48]), "+f"(d[49]), "+f"(d[50]), "+f"(d[51]), "+f"(d[52]), "+f"(d[53]), "+f"(d[54]), "+f"(d[55]), "+f"(d[56]), "+f"(d[57]), "+f"(d[58]), "+f"(d[59]), "+f"(d[60]), "+f"(d[61]), "+f"(d[62]), "+f"(d[63]), "+f"(d[64]), "+f"(d[65]), "+f"(d[66]), "+f"(d[67]), "+f"(d[68]), "+f"(d[69]), "+f"(d[70]), "+f"(d[71]), "+f"(d[72]), "+f"(d[73]), "+f"(d[74]), "+f"(d[75]), "+f"(d[76]), "+f"(d[77]), "+f"(d[78]), "+f"(d[79]), "+f"(d[80]), "+f"(d[81]), "+f"(d[82]), "+f"(d[83]), "+f"(d[84]), "+f"(d[85]), "+f"(d[86]), "+f"(d[87]), "+f"(d[88]), "+f"(d[89]), "+f"(d[90]), "+f"(d[91]), "+f"(d[92]), "+f"(d[93]), "+f"(d[94]), "+f"(d[95])
    : "l"(descA), "l"(descB), "r"(scaleD));
}
__device__ __forceinline__ void wgmma_n48_ss_ta0_tb1(float (&d)[24], uint64_t descA, uint64_t descB, int scaleD) {
  asm volatile("{\n.reg .pred p;\n"
    "setp.ne.b32 p, %26, 0;\n"
    "wgmma.mma_async.sync.aligned.m64n48k16.f32.bf16.bf16 "
    "{%0, %1, %2, %3, %4, %5, %6, %7, %8, %9, %10, %11, %12, %13, %14, %15, %16, %17, %18, %19, %20, %21, %22, %23}, "
    "%24, %25, p, 1, 1, 0, 1;\n}\n"
    : "+f"(d[0]), "+f"(d[1]), "+f"(d[2]), "+f"(d[3]), "+f"(d[4]), "+f"(d[5]), "+f"(d[6]), "+f"(d[7]), "+f"(d[8]), "+f"(d[9]), "+f"(d[10]), "+f"(d[11]), "+f"(d[12]), "+f"(d[13]), "+f"(d[14]), "+f"(d[15]), "+f"(d[16]), "+f"(d[17]), "+f"(d[18]), "+f"(d[19]), "+f"(d[20]), "+f"(d[21]), "+f"(d[22]), "+f"(d[23])
    : "l"(descA), "l"(descB), "r"(scaleD));
}
__device__ __forceinline__ void wgmma_n88_ss_ta1_tb1(float (&d)[44], uint64_t descA, uint64_t descB, int scaleD) {
  asm volatile("{\n.reg .pred p;\n"
    "setp.ne.b32 p, %46, 0;\n"
    "wgmma.mma_async.sync.aligned.m64n88k16.f32.bf16.bf16 "
    "{%0, %1, %2, %3, %4, %5, %6, %7, %8, %9, %10, %11, %12, %13, %14, %15, %16, %17, %18, %19, %20, %21, %22, %23, %24, %25, %26, %27, %28, %29, %30, %31, %32, %33, %34, %35, %36, %37, %38, %39, %40, %41, %42, %43}, "
    "%44, %45, p, 1, 1, 1, 1;\n}\n"
    : "+f"(d[0]), "+f"(d[1]), "+f"(d[2]), "+f"(d[3]), "+f"(d[4]), "+f"(d[5]), "+f"(d[6]), "+f"(d[7]), "+f"(d[8]), "+f"(d[9]), "+f"(d[10]), "+f"(d[11]), "+f"(d[12]), "+f"(d[13]), "+f"(d[14]), "+f"(d[15]), "+f"(d[16]), "+f"(d[17]), "+f"(d[18]), "+f"(d[19]), "+f"(d[20]), "+f"(d[21]), "+f"(d[22]), "+f"(d[23]), "+f"(d[24]), "+f"(d[25]), "+f"(d[26]), "+f"(d[27]), "+f"(d[28]), "+f"(d[29]), "+f"(d[30]), "+f"(d[31]), "+f"(d[32]), "+f"(d[33]), "+f"(d[34]), "+f"(d[35]), "+f"(d[36]), "+f"(d[37]), "+f"(d[38]), "+f"(d[39]), "+f"(d[40]), "+f"(d[41]), "+f"(d[42]), "+f"(d[43])
    : "l"(descA), "l"(descB), "r"(scaleD));
}
__device__ __forceinline__ void wgmma_n88_rs_ta0_tb1(float (&d)[44], uint32_t a0, uint32_t a1, uint32_t a2, uint32_t a3, uint64_t descB, int scaleD) {
  asm volatile("{\n.reg .pred p;\n"
    "setp.ne.b32 p, %49, 0;\n"
    "wgmma.mma_async.sync.aligned.m64n88k16.f32.bf16.bf16 "
    "{%0, %1, %2, %3, %4, %5, %6, %7, %8, %9, %10, %11, %12, %13, %14, %15, %16, %17, %18, %19, %20, %21, %22, %23, %24, %25, %26, %27, %28, %29, %30, %31, %32, %33, %34, %35, %36, %37, %38, %39, %40, %41, %42, %43}, "
    "{%44, %45, %46, %47}, %48, p, 1, 1, 1;\n}\n"
    : "+f"(d[0]), "+f"(d[1]), "+f"(d[2]), "+f"(d[3]), "+f"(d[4]), "+f"(d[5]), "+f"(d[6]), "+f"(d[7]), "+f"(d[8]), "+f"(d[9]), "+f"(d[10]), "+f"(d[11]), "+f"(d[12]), "+f"(d[13]), "+f"(d[14]), "+f"(d[15]), "+f"(d[16]), "+f"(d[17]), "+f"(d[18]), "+f"(d[19]), "+f"(d[20]), "+f"(d[21]), "+f"(d[22]), "+f"(d[23]), "+f"(d[24]), "+f"(d[25]), "+f"(d[26]), "+f"(d[27]), "+f"(d[28]), "+f"(d[29]), "+f"(d[30]), "+f"(d[31]), "+f"(d[32]), "+f"(d[33]), "+f"(d[34]), "+f"(d[35]), "+f"(d[36]), "+f"(d[37]), "+f"(d[38]), "+f"(d[39]), "+f"(d[40]), "+f"(d[41]), "+f"(d[42]), "+f"(d[43])
    : "r"(a0), "r"(a1), "r"(a2), "r"(a3), "l"(descB), "r"(scaleD));
}
__device__ __forceinline__ void wgmma_n80_rs_ta0_tb1(float (&d)[40], uint32_t a0, uint32_t a1, uint32_t a2, uint32_t a3, uint64_t descB, int scaleD) {
  asm volatile("{\n.reg .pred p;\n"
    "setp.ne.b32 p, %45, 0;\n"
    "wgmma.mma_async.sync.aligned.m64n80k16.f32.bf16.bf16 "
    "{%0, %1, %2, %3, %4, %5, %6, %7, %8, %9, %10, %11, %12, %13, %14, %15, %16, %17, %18, %19, %20, %21, %22, %23, %24, %25, %26, %27, %28, %29, %30, %31, %32, %33, %34, %35, %36, %37, %38, %39}, "
    "{%40, %41, %42, %43}, %44, p, 1, 1, 1;\n}\n"
    : "+f"(d[0]), "+f"(d[1]), "+f"(d[2]), "+f"(d[3]), "+f"(d[4]), "+f"(d[5]), "+f"(d[6]), "+f"(d[7]), "+f"(d[8]), "+f"(d[9]), "+f"(d[10]), "+f"(d[11]), "+f"(d[12]), "+f"(d[13]), "+f"(d[14]), "+f"(d[15]), "+f"(d[16]), "+f"(d[17]), "+f"(d[18]), "+f"(d[19]), "+f"(d[20]), "+f"(d[21]), "+f"(d[22]), "+f"(d[23]), "+f"(d[24]), "+f"(d[25]), "+f"(d[26]), "+f"(d[27]), "+f"(d[28]), "+f"(d[29]), "+f"(d[30]), "+f"(d[31]), "+f"(d[32]), "+f"(d[33]), "+f"(d[34]), "+f"(d[35]), "+f"(d[36]), "+f"(d[37]), "+f"(d[38]), "+f"(d[39])
    : "r"(a0), "r"(a1), "r"(a2), "r"(a3), "l"(descB), "r"(scaleD));
}
__device__ __forceinline__ void wgmma_n32_rs_ta0_tb0(float (&d)[16], uint32_t a0, uint32_t a1, uint32_t a2, uint32_t a3, uint64_t descB, int scaleD) {
  asm volatile("{\n.reg .pred p;\n"
    "setp.ne.b32 p, %21, 0;\n"
    "wgmma.mma_async.sync.aligned.m64n32k16.f32.bf16.bf16 "
    "{%0, %1, %2, %3, %4, %5, %6, %7, %8, %9, %10, %11, %12, %13, %14, %15}, "
    "{%16, %17, %18, %19}, %20, p, 1, 1, 0;\n}\n"
    : "+f"(d[0]), "+f"(d[1]), "+f"(d[2]), "+f"(d[3]), "+f"(d[4]), "+f"(d[5]), "+f"(d[6]), "+f"(d[7]), "+f"(d[8]), "+f"(d[9]), "+f"(d[10]), "+f"(d[11]), "+f"(d[12]), "+f"(d[13]), "+f"(d[14]), "+f"(d[15])
    : "r"(a0), "r"(a1), "r"(a2), "r"(a3), "l"(descB), "r"(scaleD));
}
__device__ __forceinline__ void wgmma_n24_rs_ta0_tb0(float (&d)[12], uint32_t a0, uint32_t a1, uint32_t a2, uint32_t a3, uint64_t descB, int scaleD) {
  asm volatile("{\n.reg .pred p;\n"
    "setp.ne.b32 p, %17, 0;\n"
    "wgmma.mma_async.sync.aligned.m64n24k16.f32.bf16.bf16 "
    "{%0, %1, %2, %3, %4, %5, %6, %7, %8, %9, %10, %11}, "
    "{%12, %13, %14, %15}, %16, p, 1, 1, 0;\n}\n"
    : "+f"(d[0]), "+f"(d[1]), "+f"(d[2]), "+f"(d[3]), "+f"(d[4]), "+f"(d[5]), "+f"(d[6]), "+f"(d[7]), "+f"(d[8]), "+f"(d[9]), "+f"(d[10]), "+f"(d[11])
    : "r"(a0), "r"(a1), "r"(a2), "r"(a3), "l"(descB), "r"(scaleD));
}
__device__ __forceinline__ void wgmma_n16_rs_ta0_tb0(float (&d)[8], uint32_t a0, uint32_t a1, uint32_t a2, uint32_t a3, uint64_t descB, int scaleD) {
  asm volatile("{\n.reg .pred p;\n"
    "setp.ne.b32 p, %13, 0;\n"
    "wgmma.mma_async.sync.aligned.m64n16k16.f32.bf16.bf16 "
    "{%0, %1, %2, %3, %4, %5, %6, %7}, "
    "{%8, %9, %10, %11}, %12, p, 1, 1, 0;\n}\n"
    : "+f"(d[0]), "+f"(d[1]), "+f"(d[2]), "+f"(d[3]), "+f"(d[4]), "+f"(d[5]), "+f"(d[6]), "+f"(d[7])
    : "r"(a0), "r"(a1), "r"(a2), "r"(a3), "l"(descB), "r"(scaleD));
}
__device__ __forceinline__ void wgmma_n8_rs_ta0_tb0(float (&d)[4], uint32_t a0, uint32_t a1, uint32_t a2, uint32_t a3, uint64_t descB, int scaleD) {
  asm volatile("{\n.reg .pred p;\n"
    "setp.ne.b32 p, %9, 0;\n"
    "wgmma.mma_async.sync.aligned.m64n8k16.f32.bf16.bf16 "
    "{%0, %1, %2, %3}, "
    "{%4, %5, %6, %7}, %8, p, 1, 1, 0;\n}\n"
    : "+f"(d[0]), "+f"(d[1]), "+f"(d[2]), "+f"(d[3])
    : "r"(a0), "r"(a1), "r"(a2), "r"(a3), "l"(descB), "r"(scaleD));
}
__device__ __forceinline__ void wgmma_n80_ss_ta0_tb1(float (&d)[40], uint64_t descA, uint64_t descB, int scaleD) {
  asm volatile("{\n.reg .pred p;\n"
    "setp.ne.b32 p, %42, 0;\n"
    "wgmma.mma_async.sync.aligned.m64n80k16.f32.bf16.bf16 "
    "{%0, %1, %2, %3, %4, %5, %6, %7, %8, %9, %10, %11, %12, %13, %14, %15, %16, %17, %18, %19, %20, %21, %22, %23, %24, %25, %26, %27, %28, %29, %30, %31, %32, %33, %34, %35, %36, %37, %38, %39}, "
    "%40, %41, p, 1, 1, 0, 1;\n}\n"
    : "+f"(d[0]), "+f"(d[1]), "+f"(d[2]), "+f"(d[3]), "+f"(d[4]), "+f"(d[5]), "+f"(d[6]), "+f"(d[7]), "+f"(d[8]), "+f"(d[9]), "+f"(d[10]), "+f"(d[11]), "+f"(d[12]), "+f"(d[13]), "+f"(d[14]), "+f"(d[15]), "+f"(d[16]), "+f"(d[17]), "+f"(d[18]), "+f"(d[19]), "+f"(d[20]), "+f"(d[21]), "+f"(d[22]), "+f"(d[23]), "+f"(d[24]), "+f"(d[25]), "+f"(d[26]), "+f"(d[27]), "+f"(d[28]), "+f"(d[29]), "+f"(d[30]), "+f"(d[31]), "+f"(d[32]), "+f"(d[33]), "+f"(d[34]), "+f"(d[35]), "+f"(d[36]), "+f"(d[37]), "+f"(d[38]), "+f"(d[39])
    : "l"(descA), "l"(descB), "r"(scaleD));
}
__device__ __forceinline__ void wgmma_n64_rs_ta0_tb0(float (&d)[32], uint32_t a0, uint32_t a1, uint32_t a2, uint32_t a3, uint64_t descB, int scaleD) {
  asm volatile("{\n.reg .pred p;\n"
    "setp.ne.b32 p, %37, 0;\n"
    "wgmma.mma_async.sync.aligned.m64n64k16.f32.bf16.bf16 "
    "{%0, %1, %2, %3, %4, %5, %6, %7, %8, %9, %10, %11, %12, %13, %14, %15, %16, %17, %18, %19, %20, %21, %22, %23, %24, %25, %26, %27, %28, %29, %30, %31}, "
    "{%32, %33, %34, %35}, %36, p, 1, 1, 0;\n}\n"
    : "+f"(d[0]), "+f"(d[1]), "+f"(d[2]), "+f"(d[3]), "+f"(d[4]), "+f"(d[5]), "+f"(d[6]), "+f"(d[7]), "+f"(d[8]), "+f"(d[9]), "+f"(d[10]), "+f"(d[11]), "+f"(d[12]), "+f"(d[13]), "+f"(d[14]), "+f"(d[15]), "+f"(d[16]), "+f"(d[17]), "+f"(d[18]), "+f"(d[19]), "+f"(d[20]), "+f"(d[21]), "+f"(d[22]), "+f"(d[23]), "+f"(d[24]), "+f"(d[25]), "+f"(d[26]), "+f"(d[27]), "+f"(d[28]), "+f"(d[29]), "+f"(d[30]), "+f"(d[31])
    : "r"(a0), "r"(a1), "r"(a2), "r"(a3), "l"(descB), "r"(scaleD));
}
__device__ __forceinline__ void wgmma_n56_rs_ta0_tb0(float (&d)[28], uint32_t a0, uint32_t a1, uint32_t a2, uint32_t a3, uint64_t descB, int scaleD) {
  asm volatile("{\n.reg .pred p;\n"
    "setp.ne.b32 p, %33, 0;\n"
    "wgmma.mma_async.sync.aligned.m64n56k16.f32.bf16.bf16 "
    "{%0, %1, %2, %3, %4, %5, %6, %7, %8, %9, %10, %11, %12, %13, %14, %15, %16, %17, %18, %19, %20, %21, %22, %23, %24, %25, %26, %27}, "
    "{%28, %29, %30, %31}, %32, p, 1, 1, 0;\n}\n"
    : "+f"(d[0]), "+f"(d[1]), "+f"(d[2]), "+f"(d[3]), "+f"(d[4]), "+f"(d[5]), "+f"(d[6]), "+f"(d[7]), "+f"(d[8]), "+f"(d[9]), "+f"(d[10]), "+f"(d[11]), "+f"(d[12]), "+f"(d[13]), "+f"(d[14]), "+f"(d[15]), "+f"(d[16]), "+f"(d[17]), "+f"(d[18]), "+f"(d[19]), "+f"(d[20]), "+f"(d[21]), "+f"(d[22]), "+f"(d[23]), "+f"(d[24]), "+f"(d[25]), "+f"(d[26]), "+f"(d[27])
    : "r"(a0), "r"(a1), "r"(a2), "r"(a3), "l"(descB), "r"(scaleD));
}
__device__ __forceinline__ void wgmma_n48_rs_ta0_tb0(float (&d)[24], uint32_t a0, uint32_t a1, uint32_t a2, uint32_t a3, uint64_t descB, int scaleD) {
  asm volatile("{\n.reg .pred p;\n"
    "setp.ne.b32 p, %29, 0;\n"
    "wgmma.mma_async.sync.aligned.m64n48k16.f32.bf16.bf16 "
    "{%0, %1, %2, %3, %4, %5, %6, %7, %8, %9, %10, %11, %12, %13, %14, %15, %16, %17, %18, %19, %20, %21, %22, %23}, "
    "{%24, %25, %26, %27}, %28, p, 1, 1, 0;\n}\n"
    : "+f"(d[0]), "+f"(d[1]), "+f"(d[2]), "+f"(d[3]), "+f"(d[4]), "+f"(d[5]), "+f"(d[6]), "+f"(d[7]), "+f"(d[8]), "+f"(d[9]), "+f"(d[10]), "+f"(d[11]), "+f"(d[12]), "+f"(d[13]), "+f"(d[14]), "+f"(d[15]), "+f"(d[16]), "+f"(d[17]), "+f"(d[18]), "+f"(d[19]), "+f"(d[20]), "+f"(d[21]), "+f"(d[22]), "+f"(d[23])
    : "r"(a0), "r"(a1), "r"(a2), "r"(a3), "l"(descB), "r"(scaleD));
}
__device__ __forceinline__ void wgmma_n40_rs_ta0_tb0(float (&d)[20], uint32_t a0, uint32_t a1, uint32_t a2, uint32_t a3, uint64_t descB, int scaleD) {
  asm volatile("{\n.reg .pred p;\n"
    "setp.ne.b32 p, %25, 0;\n"
    "wgmma.mma_async.sync.aligned.m64n40k16.f32.bf16.bf16 "
    "{%0, %1, %2, %3, %4, %5, %6, %7, %8, %9, %10, %11, %12, %13, %14, %15, %16, %17, %18, %19}, "
    "{%20, %21, %22, %23}, %24, p, 1, 1, 0;\n}\n"
    : "+f"(d[0]), "+f"(d[1]), "+f"(d[2]), "+f"(d[3]), "+f"(d[4]), "+f"(d[5]), "+f"(d[6]), "+f"(d[7]), "+f"(d[8]), "+f"(d[9]), "+f"(d[10]), "+f"(d[11]), "+f"(d[12]), "+f"(d[13]), "+f"(d[14]), "+f"(d[15]), "+f"(d[16]), "+f"(d[17]), "+f"(d[18]), "+f"(d[19])
    : "r"(a0), "r"(a1), "r"(a2), "r"(a3), "l"(descB), "r"(scaleD));
}
struct Params {
    const __nv_bfloat16 *u, *wqkv, *wo, *A_re, *A_im, *B_re, *B_im, *C_re, *C_im, *log_dt, *Dskip, *gate_w;
    long long* tim;
};
#define TSTAMP(slot) do { } while (0)
#define TDUMP() do { } while (0)
#define TINIT() do { } while (0)

__device__ __forceinline__ void issue_stage(const CUtensorMap* mA, const CUtensorMap* mB0, const CUtensorMap* mB1, uint32_t sb, int kb, int rb, int hg) {
    const int s = kb % NST;
    const uint32_t full = sb + OFF_MISC + B_FULL + 8 * s, st = sb + s * ST_BYTES;
    mbar_expect_tx(full, ST_BYTES);
    tma2d(st, mA, kb * 64, rb * 128, full);
    tma3d(st + 16384, mB0, hg * 80, kb * 64, 0, full);
    tma3d(st + 16384 + 24576, mB1, hg * 80 + 64, kb * 64, 0, full);
}
__device__ __forceinline__ void issue_otile(const CUtensorMap* mO, const CUtensorMap* mWo, uint32_t sb, int kb, int rb, int hg) {
    const int s = kb < 5 ? kb : kb - 5;
    const uint32_t full = sb + OFF_MISC + B_OF + 8 * s;
    mbar_expect_tx(full, kb < 5 ? 16384 : 16384 + 10240);
    tma2d(sb + oslot_off(s), mO, kb * 64, rb * 128, full);
    if (kb >= 5) tma3d(sb + OFF_WO + s * 10240, mWo, 0, kb * 64, hg * 5, full);
}
__device__ __forceinline__ void consumer_role(const Params& P, const CUtensorMap* mA, const CUtensorMap* mB0, const CUtensorMap* mB1, const CUtensorMap* mWo,
                                              const CUtensorMap* mOut, const CUtensorMap* mO, uint32_t sb, int rb, int hg) {
    const int tid = threadIdx.x, lane = tid & 31, warp = tid >> 5, wg = warp >> 2, w4 = warp & 3;
    const int g = lane >> 2, t = lane & 3;
    const uint32_t misc = sb + OFF_MISC;
    const unsigned epr = tid == 32 ? ld_relaxed(&g_cnt[(0 * 16 + hg) * 32]) : 0u;
    float acc[120];
    float (&acc192)[96] = *reinterpret_cast<float(*)[96]>(&acc[0]);
    float (&acc48)[24] = *reinterpret_cast<float(*)[24]>(&acc[96]);
#pragma unroll
    for (int i = 0; i < 120; i++) acc[i] = 0.f;
#pragma unroll 1
    for (int kb = 0, s = 0, ph = 0; kb < 10; kb++) {
        mbar_wait(misc + B_FULL + 8 * s, ph);
        const uint32_t st = sb + s * ST_BYTES;
        const uint32_t sa = st + wg * 8192, sbb = st + 16384;
        wg_fence();
#pragma unroll
        for (int ks = 0; ks < 4; ks++) {
            const uint64_t da = make_desc(sa + ks * 32, 16, 1024, 1);
            wgmma_n192_ss_ta0_tb1(acc192, da, make_desc(sbb + ks * 2048, 8192, 1024, 1), 1);
            wgmma_n48_ss_ta0_tb1(acc48, da, make_desc(sbb + 24576 + ks * 512, 2048, 256, 3), 1);
        }
        wg_commit();
        if (kb > 0) {
            wg_wait<1>();
            if ((tid & 127) == 0 && kb <= 7 && (atom_inc_cta(misc + M_STG + 4 * (s == 0 ? NST - 1 : s - 1)) & 1)) issue_stage(mA, mB0, mB1, sb, kb + 2, rb, hg);
        }
        if (++s == NST) { s = 0; ph ^= 1; }
    }
    wg_wait<0>();
    if (tid == 0) TSTAMP(1);
    {
        uint32_t pk[20], vv[20];
#pragma unroll
        for (int j = 0; j < 10; j++) {
            const int bk = j < 8 ? 32 + 4 * j : 104 + 4 * (j - 8);
            const int bv = j < 8 ? 64 + 4 * j : 112 + 4 * (j - 8);
            pk[2 * j] = phi2(acc[bk], acc[bk + 1]); pk[2 * j + 1] = phi2(acc[bk + 2], acc[bk + 3]);
            vv[2 * j] = pack_bf16(acc[bv], acc[bv + 1]); vv[2 * j + 1] = pack_bf16(acc[bv + 2], acc[bv + 3]);
        }
        if (tid == 32) sts32(misc + M_EPOCH, epr >> 4);
        bar_sync(1, 256);
        if (tid == 0) TSTAMP(10);
        const int m = lane >> 3, row = 64 * wg + 16 * w4 + (lane & 7) + 8 * (m & 1);
        const uint32_t off = row * 32 + (((m >> 1) ^ ((row >> 2) & 1)) << 4);
#pragma unroll
        for (int cg = 0; cg < 5; cg++) {
            stsm_x4(sb + OFF_PK + cg * 4096 + off, pk[4 * cg], pk[4 * cg + 1], pk[4 * cg + 2], pk[4 * cg + 3]);
            stsm_x4(sb + OFF_V + cg * 4096 + off, vv[4 * cg], vv[4 * cg + 1], vv[4 * cg + 2], vv[4 * cg + 3]);
        }
        const int r2 = tid >> 1, h = (tid & 1) ^ ((r2 >> 2) & 1);
        sts128(sb + OFF_ONES + tid * 16, h == 0 ? 0x00003F80u : 0u, 0u, 0u, 0u);
    }
    fence_async();
    bar_sync(1, 256);
    if (tid == 0) TSTAMP(11);
    const unsigned ep = lds32(misc + M_EPOCH);
    float* kvg = g_kvacc + ((ep & 1) * 8 + hg) * KV_STRIDE;
    {
        float kv[44];
        wg_fence();
#pragma unroll
        for (int ks = 0; ks < 8; ks++)
            wgmma_n88_ss_ta1_tb1(kv, make_desc(sb + OFF_PK + wg * 16384 + ks * 512, 4096, 256, 3), make_desc(sb + OFF_V + ks * 512, 4096, 256, 3), ks > 0);
        wg_commit();
        wg_wait<0>();
        if (tid == 0) TSTAMP(13);
        if (wg == 0 || w4 == 0) {
#pragma unroll
            for (int hh = 0; hh < 2; hh++) {
                const int d = 64 * wg + 16 * w4 + g + 8 * hh, h = d / 20;
                const uint32_t rowp = sb + OFF_KVST + (d * 20 - 20 * h + 2 * t) * 4;
#pragma unroll
                for (int j = 0; j < 10; j++) {
                    const int c = 8 * j + 2 * t - 20 * h;
                    if (c >= 0 && c < 20) sts64f(rowp + 32 * j, kv[4 * j + 2 * hh], kv[4 * j + 2 * hh + 1]);
                }
                if (t == 0) sts32f(sb + OFF_KVST + (1600 + d) * 4, kv[40 + 2 * hh]);
            }
        }
    }
    fence_async();
    bar_sync(1, 256);
    if (tid == 0) {
        TSTAMP(15);
        bulk_reduce_add_f32(kvg, sb + OFF_KVST, 6720);
        bulk_commit();
        bulk_wait0();
        TSTAMP(16);
        red_release(&g_cnt[(0 * 16 + hg) * 32], 1u);
        TSTAMP(2);
    }
    uint32_t pq[20];
#pragma unroll
    for (int j = 0; j < 10; j++) {
        const int bq = j < 8 ? 4 * j : 96 + 4 * (j - 8);
        pq[2 * j] = phi2(acc[bq], acc[bq + 1]); pq[2 * j + 1] = phi2(acc[bq + 2], acc[bq + 3]);
    }
#pragma unroll
    for (int it = 0; it < 4; it++) { const int id = tid + 256 * it; if (id < 960) sts128(sb + OFF_KVB + id * 16, 0u, 0u, 0u, 0u); }
    if (tid == 0) TSTAMP(18);
    bar_sync(1, 256);
    if (tid == 0) TSTAMP(19);
    if (tid == 64) {
        mbar_expect_tx(misc + B_WO, 5 * 10240);
#pragma unroll 1
        for (int kb = 0; kb < 5; kb++) tma3d(sb + OFF_WO + kb * 10240, mWo, 0, kb * 64, hg * 5, misc + B_WO);
    }
    {
        const int row = 128 * rb + 16 * hg + 2 * warp;
        uint2 wv[5], a[2][5];
#pragma unroll
        for (int i = 0; i < 5; i++) {
            wv[i] = __ldg(reinterpret_cast<const uint2*>(P.gate_w) + lane + 32 * i);
            a[0][i] = __ldg(reinterpret_cast<const uint2*>(P.u + (size_t)row * DM) + lane + 32 * i);
            a[1][i] = __ldg(reinterpret_cast<const uint2*>(P.u + (size_t)(row + 1) * DM) + lane + 32 * i);
        }
        float s[2] = {0.f, 0.f};
#pragma unroll
        for (int r = 0; r < 2; r++)
#pragma unroll
            for (int i = 0; i < 5; i++) {
                const uint32_t p = hmul2_rn(a[r][i].x, wv[i].x), q = hmul2_rn(a[r][i].y, wv[i].y);
                s[r] += (bf_lo(p) + bf_hi(p)) + (bf_lo(q) + bf_hi(q));
            }
#pragma unroll
        for (int o = 16; o > 0; o >>= 1) { s[0] += __shfl_xor_sync(0xffffffffu, s[0], o); s[1] += __shfl_xor_sync(0xffffffffu, s[1], o); }
        if (lane == 0) {
            const uint32_t sr = pack_bf16(s[0], s[1]);
            *reinterpret_cast<uint32_t*>(g_gate + row) = pack_bf16(1.f / (1.f + __expf(-bf_lo(sr))), 1.f / (1.f + __expf(-bf_hi(sr))));
        }
        if (warp == 7 && lane < 28) reinterpret_cast<float4*>(g_kvacc + (((ep + 1) & 1) * 8 + hg) * KV_STRIDE + rb * 112)[lane] = make_float4(0.f, 0.f, 0.f, 0.f);
    }
    if (lane == 0) wait_counter(&g_cnt[(0 * 16 + hg) * 32], (ep + 1) * 16);
    __syncwarp();
    if (tid == 0) TSTAMP(3);
    {
        const int d0 = tid / 5, u0 = tid - 5 * d0;
        const int id1 = tid + 256, d1 = id1 / 5, u1 = id1 - 5 * d1;
        const float4 v0 = __ldcg(reinterpret_cast<const float4*>(kvg) + tid);
        float4 v1 = make_float4(0.f, 0.f, 0.f, 0.f);
        if (tid < 144) v1 = __ldcg(reinterpret_cast<const float4*>(kvg) + id1);
        else if (tid < 224) v1.x = __ldcg(kvg + 1600 + tid - 144);
        {
            const int n = 20 * (d0 / 20) + 4 * u0;
            sts64(sb + OFF_KVB + (n >> 4) * 2560 + d0 * 32 + ((((n >> 3) & 1) ^ ((d0 >> 2) & 1)) << 4) + (n & 7) * 2, pack_bf16(v0.x, v0.y), pack_bf16(v0.z, v0.w));
        }
        if (tid < 144) {
            const int n = 20 * (d1 / 20) + 4 * u1;
            sts64(sb + OFF_KVB + (n >> 4) * 2560 + d1 * 32 + ((((n >> 3) & 1) ^ ((d1 >> 2) & 1)) << 4) + (n & 7) * 2, pack_bf16(v1.x, v1.y), pack_bf16(v1.z, v1.w));
        } else if (tid < 224) {
            const int d = tid - 144;
            sts16(sb + OFF_KVB + 5 * 2560 + d * 32 + (((d >> 2) & 1) << 4) + (d / 20) * 2, pack_bf16(v1.x, 0.f));
        }
    }
    if (tid == 0) TSTAMP(20);
    fence_async();
    bar_sync(1, 256);
    if (tid == 0) TSTAMP(21);
    {
        float nm[44];
        wg_fence();
#pragma unroll
        for (int ks = 0; ks < 5; ks++)
            wgmma_n88_rs_ta0_tb1(nm, pq[4 * ks], pq[4 * ks + 1], pq[4 * ks + 2], pq[4 * ks + 3], make_desc(sb + OFF_KVB + ks * 512, 2560, 256, 3), ks > 0);
        wg_commit();
        wg_wait<0>();
        if (tid == 0) TSTAMP(22);
        float rden[2][4];
#pragma unroll
        for (int hh = 0; hh < 2; hh++) {
#pragma unroll
            for (int h = 0; h < 4; h++) {
                float x = __shfl_sync(0xffffffffu, nm[40 + 2 * hh + (h & 1)], (lane & ~3) + (h >> 1));
                x = bf_lo(pack_bf16(x, 0.f)) + 1e-6f;
                rden[hh][h] = rcp_fast(bf_lo(pack_bf16(x, 0.f)));
            }
        }
        uint32_t ov[20];
#pragma unroll
        for (int j = 0; j < 10; j++) {
#pragma unroll
            for (int hh = 0; hh < 2; hh++) {
                float dn;
                if (j == 2) dn = t < 2 ? rden[hh][0] : rden[hh][1];
                else if (j == 7) dn = t < 2 ? rden[hh][2] : rden[hh][3];
                else dn = rden[hh][(8 * j) / 20];
                const uint32_t n2 = pack_bf16(nm[4 * j + 2 * hh], nm[4 * j + 2 * hh + 1]);
                ov[2 * j + hh] = pack_bf16(bf_lo(n2) * dn, bf_hi(n2) * dn);
            }
        }
        const int m = lane >> 3, row = 64 * wg + 16 * w4 + (lane & 7) + 8 * (m & 1);
#pragma unroll
        for (int cg = 0; cg < 5; cg++)
            stsm_x4(sb + OFF_OST + row * 160 + cg * 32 + (m >> 1) * 16, ov[4 * cg], ov[4 * cg + 1], ov[4 * cg + 2], ov[4 * cg + 3]);
        __syncwarp();
        const int r0 = 64 * wg + 16 * w4;
#pragma unroll
        for (int i = 0; i < 5; i++) {
            const int c = lane + 32 * i, r = c / 10, cc = c - 10 * r;
            stg128(g_o + (size_t)(128 * rb + r0 + r) * DM + 80 * hg + 8 * cc, lds128(sb + OFF_OST + (r0 + r) * 160 + cc * 16));
        }
    }
    if (tid == 0) TSTAMP(23);
    bar_sync(3 + wg, 128);
    if ((tid & 127) == 0) {
        red_release(&g_cnt[(1 * 16 + rb) * 32], 1u);
        if (tid == 0) TSTAMP(4);
    }
    if (lane == 0 && warp < 5) {
        wait_counter(&g_cnt[(1 * 16 + rb) * 32], (ep + 1) * 16);
        if (tid == 0) TSTAMP(5);
        fence_async_global();
        issue_otile(mO, mWo, sb, warp, rb, hg);
    }
    __syncwarp();
    float fa[40];
    mbar_wait(misc + B_WO, 0);
    mbar_wait(misc + B_OF, 0);
    const uint32_t g0 = __ldcg(reinterpret_cast<const unsigned short*>(g_gate) + 128 * rb + 64 * wg + 16 * w4 + g);
    const uint32_t g1 = __ldcg(reinterpret_cast<const unsigned short*>(g_gate) + 128 * rb + 64 * wg + 16 * w4 + g + 8);
#pragma unroll 1
    for (int kb = 0; kb < 10; kb++) {
        const int s = kb < 5 ? kb : kb - 5;
        mbar_wait(misc + B_OF + 8 * s, kb >= 5);
        if (tid == 0 && (kb & 1) == 0) TSTAMP(30 + (kb >> 1));
        const uint32_t sa = sb + oslot_off(s) + wg * 8192, w = sb + OFF_WO + s * 10240;
        wg_fence();
#pragma unroll
        for (int ks = 0; ks < 4; ks++)
            wgmma_n80_ss_ta0_tb1(fa, make_desc(sa + ks * 32, 16, 1024, 1), make_desc(w + ks * 512, 2048, 256, 3), (kb | ks) != 0);
        wg_commit();
        if (kb > 0 && kb <= 5) {
            wg_wait<1>();
            if ((tid & 127) == 0 && (atom_inc_cta(misc + M_OSTG + 4 * (kb - 1)) & 1)) { fence_async_global(); issue_otile(mO, mWo, sb, kb + 4, rb, hg); }
        }
    }
    wg_wait<0>();
    if (tid == 0) TSTAMP(6);
    bar_sync(1, 256);
    mbar_wait(misc + B_AT, 0);
    if (tid == 0) TSTAMP(7);
    {
        const uint32_t gg[2] = {g0 | (g0 << 16), g1 | (g1 << 16)};
        const uint32_t om[2] = {hsub2_rn(0x3F803F80u, gg[0]), hsub2_rn(0x3F803F80u, gg[1])};
        const int m = lane >> 3, r = lane & 7;
        const int row = 64 * wg + 16 * w4 + r + 8 * (m & 1);
#pragma unroll
        for (int cg = 0; cg < 5; cg++) {
            uint32_t a[4];
            const int ch = 16 * cg + 8 * (m >> 1) + r;
            ldsm_x4_t(sb + OFF_AT + wg * 10240 + ch * 128 + (((2 * w4 + (m & 1)) ^ (ch & 7)) << 4), a[0], a[1], a[2], a[3]);
            uint32_t o[4];
#pragma unroll
            for (int q = 0; q < 4; q++) {
                const int j = 2 * cg + (q >> 1), hh = q & 1;
                const uint32_t b2 = pack_bf16(fa[4 * j + 2 * hh], fa[4 * j + 2 * hh + 1]);
                o[q] = hadd2_rn(hmul2_rn(gg[hh], a[q]), hmul2_rn(om[hh], b2));
            }
            stsm_x4(sb + OFF_OST + row * 160 + cg * 32 + (m >> 1) * 16, o[0], o[1], o[2], o[3]);
        }
    }
    fence_async();
    bar_sync(3 + wg, 128);
    if ((tid & 127) == 0) {
        tma_store2d(mOut, sb + OFF_OST + wg * 64 * 160, 80 * hg, 128 * rb + 64 * wg);
        bulk_commit();
        bulk_wait0();
        if (tid == 0) TSTAMP(8);
    }
}

__device__ __forceinline__ void load_late_tiles(const CUtensorMap* mAT, uint32_t sb, int rb, int hg, unsigned ep) {
    const uint32_t misc = sb + OFF_MISC;
    mbar_wait(misc + B_CONV, 0);
    wait_counter(&g_cnt[(2 * 16 + hg) * 32], (ep + 1) * 32);
    fence_async_global();
    mbar_expect_tx(misc + B_AT, 20480);
    tma2d(sb + OFF_AT, mAT, rb * 128, hg * 80, misc + B_AT);
    tma2d(sb + OFF_AT + 10240, mAT, rb * 128 + 64, hg * 80, misc + B_AT);
}
__device__ __forceinline__ float bf_ld(const __nv_bfloat16* p) { return __uint_as_float((uint32_t)__ldg(reinterpret_cast<const unsigned short*>(p)) << 16); }
struct cpx { float x, y; };
__device__ __forceinline__ cpx cmul(cpx a, cpx b) { cpx r; r.x = fmaf(a.x, b.x, -a.y * b.y); r.y = fmaf(a.x, b.y, a.y * b.x); return r; }
__device__ __forceinline__ cpx csqr(cpx a) { cpx r; r.x = fmaf(a.x, a.x, -a.y * a.y); r.y = (a.x + a.x) * a.y; return r; }
__device__ __forceinline__ cpx cexp_v(float ar2, float ai, float v) {
    const float m = ex2f(ar2 * v), ph = ai * v;
    cpx r; r.x = m * __cosf(ph); r.y = m * __sinf(ph); return r;
}
__device__ __forceinline__ uint32_t pk_a(cpx a) { return pack_bf16(a.x, a.y); }
__device__ __forceinline__ uint32_t pk_b(cpx a) { return pack_bf16(a.x, -a.y); }

__device__ __forceinline__ void aux_transpose_u(uint32_t sb, int rb, int hg, int w4, int lane) {
    mbar_wait(sb + OFF_MISC + B_U0, 0);
    const uint32_t a = sb + OFF_UT + (32 * (lane >> 3) + 8 * w4 + (lane & 7)) * 160;
    uint32_t* dst = reinterpret_cast<uint32_t*>(g_uT + ((size_t)(80 * hg + (lane >> 2)) * 4 + w4) * 512 + (63 - 4 * rb) * 8) + (lane & 3);
#pragma unroll 2
    for (int c = 0; c < 10; c++) {
        uint32_t r0, r1, r2, r3;
        ldsm_x4_t(a + c * 16, r0, r1, r2, r3);
        uint32_t* d = dst + (size_t)c * (8 * 1024);
        d[0] = r0; d[-4] = r1; d[-8] = r2; d[-12] = r3;
    }
}

__device__ __forceinline__ uint32_t ldg16(const void* p) { uint16_t v; asm volatile("ld.global.nc.u16 %0, [%1];" : "=h"(v) : "l"(p)); return v; }
__device__ __forceinline__ uint32_t lds16(uint32_t addr) { uint16_t v; asm volatile("ld.shared.u16 %0, [%1];" : "=h"(v) : "r"(addr) : "memory"); return v; }
__device__ __forceinline__ void aux_stage_params(const Params& P, uint32_t sb, int ch0, int wgi, int w4, int lane) {
#pragma unroll 1
    for (int r = 2 * w4 + (lane >> 4); r < 18 - 6 * wgi; r += 8) {
        const int cl = r / 6, a = r - 6 * cl, c = wgi ? 2 + cl : (cl < 2 ? cl : 4);
        const uint8_t* src = reinterpret_cast<const uint8_t* const*>(&P.A_re)[a] + (ch0 + c) * 256 + (lane & 15) * 16;
        asm volatile("cp.async.cg.shared.global [%0], [%1], 16;" :: "r"(sb + OFF_PS + (c * 6 + a) * 256 + (lane & 15) * 16), "l"(src) : "memory");
    }
}
__device__ __noinline__ void aux_kgen_b(uint32_t ps, float ldt, uint32_t cst, uint32_t b) {
    float r[6];
#pragma unroll
    for (int i = 0; i < 6; i++) r[i] = bf_lo(lds16(ps + i * 256));
    const float dt = bf_lo(pack_bf16(expf(ldt), 0.f));
    const float ar2 = dt * r[0] * 1.4426950408889634f, ai = dt * r[1];
    const float dbx = dt * r[2], dby = dt * r[3];
    cpx c; c.x = fmaf(r[4], dbx, -r[5] * dby); c.y = -fmaf(r[4], dby, r[5] * dbx);
    const float an = -ai;
    const cpx e64 = cexp_v(ar2, ai, 64.f), e1 = cexp_v(ar2, an, 1.f), e256 = cexp_v(ar2, an, 256.f);
    sts128f(cst, ar2, ai, e64.x, e64.y);
    sts32(b + 20 * 16, pk_a(c));
    cpx x = c;
#pragma unroll
    for (int q = 0; q < 8; q++) { x = cmul(x, e1); sts32(b + q * 16, pk_a(x)); }
    const cpx e2 = csqr(e1), e4 = csqr(e2);
    x = cmul(c, cexp_v(ar2, an, 258.f)); sts32(b + 8 * 16, pk_a(x));
#pragma unroll
    for (int q = 0; q < 3; q++) { x = cmul(x, e2); sts32(b + (9 + q) * 16, pk_a(x)); }
    x = cmul(c, cexp_v(ar2, an, 516.f)); sts32(b + 12 * 16, pk_a(x));
    sts32(b + 13 * 16, pk_a(cmul(x, e4)));
    x = cmul(x, e256); sts32(b + 14 * 16, pk_a(x));
    sts32(b + 15 * 16, pk_a(cmul(x, e4)));
    x = cmul(c, cexp_v(ar2, an, 1032.f)); sts32(b + 16 * 16, pk_a(x));
#pragma unroll
    for (int q = 0; q < 3; q++) { x = cmul(x, e256); sts32(b + (17 + q) * 16, pk_a(x)); }
}
__device__ __forceinline__ void aux_kgen(int tsb, bool rel, int hg, uint32_t ps, uint32_t ld01, bool split, uint32_t ks, uint32_t kb0, uint32_t kx, int barid, int w4, int lane, int s) {
    {
        const int sl = split ? s & 63 : s, x1 = split ? (s >> 6) + 1 : 2;
#pragma unroll 1
        for (int x = split ? s >> 6 : 0; x < x1; x++)
            aux_kgen_b(ps + x * (split ? 128 : 1536) + sl * 2, x ? bf_hi(ld01) : bf_lo(ld01), ks + KS_CST + x * 2048 + sl * 16, ks + (sl >> 2) * KS_PITCH + (sl & 3) * 4 + x * (24 * 16));
    }
    if (s == 0) TSTAMP(tsb);
    fence_async();
    bar_sync(barid, 128);
    if (s == 0) TSTAMP(tsb + 1);
    if (s == 0 && rel) red_release(&g_cnt[(3 * 16 + hg) * 32], 1u);
    const int g = lane >> 2, t = lane & 3, sel = w4 >> 1;
    const float vj = (float)(8 * (16 * (w4 & 1) + g));
    uint32_t dlo = ((ks & 0x3FFFF) >> 4) | ((KS_PITCH >> 4) << 16);
    uint32_t ca = ks + KS_CST + sel * 2048 + t * 16;
    float acc[24];
#pragma unroll
    for (int i = 0; i < 24; i++) acc[i] = 0.f;
    uint32_t Q[2][2][4];
    const int nit = split ? 2 : 4;
#pragma unroll 1
    for (int it = 0; it < nit; it++) {
#pragma unroll
        for (int gi = 0; gi < 2; gi++) {
            float4 cs[4];
#pragma unroll
            for (int i = 0; i < 4; i++) cs[i] = lds128f(ca + (16 * gi + 4 * i) * 16);
            wg_wait<1>();
#pragma unroll
            for (int kk = 0; kk < 2; kk++)
#pragma unroll
                for (int h = 0; h < 2; h++) {
                    const float4 c4 = cs[2 * kk + h];
                    const cpx x = cexp_v(c4.x, c4.y, vj);
                    Q[gi][kk][2 * h] = pk_a(x);
                    Q[gi][kk][2 * h + 1] = pk_a(cmul(x, cpx{c4.z, c4.w}));
                }
            wg_fence();
#pragma unroll
            for (int kk = 0; kk < 2; kk++)
                wgmma_n48_rs_ta0_tb0(acc, Q[gi][kk][0], Q[gi][kk][1], Q[gi][kk][2], Q[gi][kk][3],
                                     (uint64_t)(dlo + (2 * gi + kk) * (2 * KS_PITCH >> 4)) | ((uint64_t)(128 >> 4) << 32), 1);
            wg_commit();
        }
        dlo += 4 * (2 * KS_PITCH >> 4); ca += 512;
    }
    wg_wait<0>();
    if (s == 0) TSTAMP(tsb + 2);
    float d[12];
#pragma unroll
    for (int i = 0; i < 12; i++) d[i] = sel ? acc[12 + i] : acc[i];
    if (split) {
        const uint32_t xa = kx + ((w4 & 1) * 32 + lane) * 4;
        if (sel) {
#pragma unroll
            for (int i = 0; i < 12; i++) sts32f(xa + i * 256, d[i]);
        }
        bar_sync(barid, 128);
        if (!sel) {
#pragma unroll
            for (int i = 0; i < 12; i++) d[i] += lds32f(xa + i * 256);
        }
    }
    if (!split || !sel) {
        const uint32_t kb = kb0 + sel * KB_BYTES;
#pragma unroll
        for (int hh = 0; hh < 2; hh++) {
            const int j = 16 * (w4 & 1) + g + 8 * hh;
            const uint32_t p0 = pack_bf16(d[2 * hh], d[2 * hh + 1]), p1 = pack_bf16(d[4 + 2 * hh], d[5 + 2 * hh]), p2 = pack_bf16(d[8 + 2 * hh], d[9 + 2 * hh]);
            sts32(kb + (2 + 8 * j + 2 * t) * 2, p0);
            sts32(kb + (t < 2 ? 258 + 4 * j + 2 * t : 386 + 2 * j + 64 * (t - 2)) * 2, p1);
            if (t < 2) { sts16(kb + (514 + j + 64 * t) * 2, p2); sts16(kb + (546 + j + 64 * t) * 2, p2 >> 16); }
            else if (t == 2 && j == 0) sts32(kb, p2 << 16);
        }
    }
    bar_sync(barid, 128);
}
__device__ __forceinline__ void aux_phase1(const Params& P, const CUtensorMap* mU, const CUtensorMap* mUT, uint32_t sb, int rb, int hg, int wgi, int w4, int lane, int t128) {
    const int ch0 = 80 * hg + 5 * rb;
    if (wgi == 0 && t128 == 0) TSTAMP(57);
    aux_stage_params(P, sb, ch0, wgi, w4, lane);
    const unsigned short* ldp = reinterpret_cast<const unsigned short*>(P.log_dt) + ch0;
    const uint32_t ld0 = ldg16(ldp + 2 * wgi), ld1 = ldg16(ldp + 2 * wgi + 1);
    const uint32_t ld4 = ldg16(ldp + 4);
    if (wgi == 0 && t128 == 0) TSTAMP(63);
    unsigned epr = 0;
    if (wgi == 1 && t128 == 0) {
        mbar_init(sb + OFF_MISC + B_U0, 1);
        asm volatile("fence.mbarrier_init.release.cluster;" ::: "memory");
        mbar_expect_tx(sb + OFF_MISC + B_U0, 20480);
        tma2d(sb + OFF_UT, mU, 80 * hg, 128 * rb, sb + OFF_MISC + B_U0);
        epr = ld_relaxed(&g_cnt[(3 * 16 + hg) * 32]);
    }
    __syncwarp();
    if (wgi == 0) bar_arrive(0, 512);
    else {
        aux_transpose_u(sb, rb, hg, w4, lane);
        if (t128 == 0) TSTAMP(62);
        bar_sync(0, 512);
    }
    asm volatile("cp.async.wait_all;" ::: "memory");
    bar_sync(6 + wgi, 128);
    if (wgi == 0 && t128 == 0) TSTAMP(54);
    uint32_t ld01 = ld0 | (ld1 << 16);
    const uint32_t ld44 = ld4 | (ld4 << 16);
#pragma unroll 1
    for (int it = 0; it < 2 - wgi; it++) {
        aux_kgen(wgi == 0 ? 24 + 3 * it : 58, wgi == 1, hg, sb + OFF_PS + (it == 1 ? 4 : 2 * wgi) * 1536, ld01, it == 1, sb + OFF_KS + wgi * KS_BYTES,
                 sb + OFF_KB + (it == 1 ? 4 : 2 * wgi) * KB_BYTES, sb + OFF_KX, 6 + wgi, w4, lane, t128);
        if (t128 == 0) TSTAMP(52 + 4 * wgi + it);
        ld01 = ld44;
    }
    if (wgi == 1 && t128 == 0) {
        wait_counter(&g_cnt[(3 * 16 + hg) * 32], ((epr >> 4) + 1) * 16);
        fence_async_global();
        mbar_expect_tx(sb + OFF_MISC + B_UT, 5 * UT_BYTES);
        tma2d(sb + OFF_UT, mUT, 0, (80 * hg + 5 * rb) * 4, sb + OFF_MISC + B_UT);
    }
    __syncwarp();
}

__device__ __forceinline__ void aux_tables(uint32_t sb, int t256) {
    if (t256 < 80) sts128(sb + OFF_TAB + (t256 >> 4) * TAB_BYTES + (t256 & 15) * 16, 0u, 0u, 0u, 0u);
#pragma unroll
    for (int it = 0; it < 2; it++) {
        const int p = 4 * (t256 + 256 * it);
        uint32_t pos[5];
#pragma unroll
        for (int x = 0; x < 5; x++) {
            const int j = p - 1 + x;
            const uint32_t b = pack_bf16((float)j, 0.f) & 0xFFFFu;
            pos[x] = 2 * (j < 128 ? j + 1 : (int)b - 17023);
        }
#pragma unroll
        for (int ch = 0; ch < 5; ch++) {
            uint32_t k[5];
#pragma unroll
            for (int x = 0; x < 5; x++) k[x] = lds16(sb + OFF_KB + ch * KB_BYTES + pos[x]);
            sts128(sb + OFF_TAB + ch * TAB_BYTES + (p + 64) * 4, k[1] | (k[0] << 16), k[2] | (k[1] << 16), k[3] | (k[2] << 16), k[4] | (k[3] << 16));
        }
    }
}

template <int E> __device__ __forceinline__ void conv_mma(float (&acc)[32], const uint32_t (&a)[4], uint64_t desc) {
    if constexpr (E == 0) wgmma_n64_rs_ta0_tb0(acc, a[0], a[1], a[2], a[3], desc, 1);
    else if constexpr (E == 1) wgmma_n56_rs_ta0_tb0(*reinterpret_cast<float(*)[28]>(&acc[0]), a[0], a[1], a[2], a[3], desc, 1);
    else if constexpr (E == 2) wgmma_n48_rs_ta0_tb0(*reinterpret_cast<float(*)[24]>(&acc[0]), a[0], a[1], a[2], a[3], desc, 1);
    else if constexpr (E == 3) wgmma_n40_rs_ta0_tb0(*reinterpret_cast<float(*)[20]>(&acc[0]), a[0], a[1], a[2], a[3], desc, 1);
    else if constexpr (E == 4) wgmma_n32_rs_ta0_tb0(*reinterpret_cast<float(*)[16]>(&acc[0]), a[0], a[1], a[2], a[3], desc, 1);
    else if constexpr (E == 5) wgmma_n24_rs_ta0_tb0(*reinterpret_cast<float(*)[12]>(&acc[0]), a[0], a[1], a[2], a[3], desc, 1);
    else if constexpr (E == 6) wgmma_n16_rs_ta0_tb0(*reinterpret_cast<float(*)[8]>(&acc[0]), a[0], a[1], a[2], a[3], desc, 1);
    else wgmma_n8_rs_ta0_tb0(*reinterpret_cast<float(*)[4]>(&acc[0]), a[0], a[1], a[2], a[3], desc, 1);
}
__device__ __forceinline__ void conv_load(uint32_t (&Q)[2][4], uint32_t a) {
    Q[1][2] = lds32(a); Q[1][0] = lds32(a + 32); Q[1][1] = lds32(a + 64); Q[0][0] = lds32(a + 96); Q[0][1] = lds32(a + 128);
}
__device__ __forceinline__ void conv_dup(uint32_t (&Q)[2][4]) {
    asm volatile("mov.b32 %0, %1;" : "=r"(Q[1][3]) : "r"(Q[1][0]));
    asm volatile("mov.b32 %0, %1;" : "=r"(Q[0][2]) : "r"(Q[1][1]));
    asm volatile("mov.b32 %0, %1;" : "=r"(Q[0][3]) : "r"(Q[0][0]));
}
template <int D> __device__ __forceinline__ void conv_steps(float (&acc)[32], uint32_t (&Q)[3][2][4], uint32_t rbase, uint32_t dlo) {
    conv_dup(Q[D % 3]);
    wg_fence();
#pragma unroll
    for (int ks = 0; ks < 2; ks++) {
        const uint32_t lo = dlo + (2 * ks * UT_PLANE >> 4) + 2 * D;
        conv_mma<D / 4>(acc, Q[D % 3][ks], (uint64_t)lo | ((uint64_t)(128 >> 4) << 32));
    }
    wg_commit();
    if constexpr (D + 2 < 32) {
        wg_wait<1>();
        conv_load(Q[(D + 2) % 3], rbase + (D + 2) * 256);
    }
    if constexpr (D + 1 < 32) conv_steps<D + 1>(acc, Q, rbase, dlo);
}
__device__ __forceinline__ void conv_channel(float (&acc)[32], uint32_t sb, int c, int w4, int lane) {
    const int g = lane >> 2, t = lane & 3;
    const uint32_t rbase = sb + OFF_TAB + c * TAB_BYTES + (64 - 24 + 16 * w4 + g - 2 * t) * 4;
    const uint32_t dlo = (((sb + OFF_UT + c * UT_BYTES) & 0x3FFFF) >> 4) | ((UT_PLANE >> 4) << 16);
    uint32_t Q[3][2][4];
    conv_load(Q[0], rbase); conv_load(Q[1], rbase + 256);
#pragma unroll
    for (int i = 0; i < 32; i++) acc[i] = 0.f;
    conv_steps<0>(acc, Q, rbase, dlo);
    wg_wait<0>();
}
__device__ __forceinline__ void conv_xput(const float (&acc)[32], uint32_t x, int w4, int lane) {
    const int g = lane >> 2, t = lane & 3;
    const uint32_t a = x + ((2 * t - 1) * 36 + 16 * (w4 & 1) + g) * 4;
#pragma unroll
    for (int j = 0; j < 8; j++) {
        if (j > 0 || t > 0) { sts32f(a + j * 8 * 144, acc[4 * j]); sts32f(a + j * 8 * 144 + 32, acc[4 * j + 2]); }
        sts32f(a + j * 8 * 144 + 144, acc[4 * j + 1]); sts32f(a + j * 8 * 144 + 144 + 32, acc[4 * j + 3]);
    }
    if (t == 3) { sts32f(x + (63 * 36 + 16 * (w4 & 1) + g) * 4, 0.f); sts32f(x + (63 * 36 + 16 * (w4 & 1) + g + 8) * 4, 0.f); }
}
__device__ __forceinline__ void conv_xget(float (&acc)[32], uint32_t x, int w4, int lane) {
    const int g = lane >> 2, t = lane & 3;
    const uint32_t a = x + (2 * t * 36 + 16 * w4 + g) * 4;
#pragma unroll
    for (int j = 0; j < 8; j++) {
        acc[4 * j] += lds32f(a + j * 8 * 144); acc[4 * j + 2] += lds32f(a + j * 8 * 144 + 32);
        acc[4 * j + 1] += lds32f(a + j * 8 * 144 + 144); acc[4 * j + 3] += lds32f(a + j * 8 * 144 + 144 + 32);
    }
}
__device__ __forceinline__ void conv_finish(const float (&acc)[32], uint32_t ut, uint32_t d2, int w4, int lane) {
    const int mi = lane >> 3;
#pragma unroll
    for (int jj = 0; jj < 4; jj++) {
        const uint32_t a = ut + (2 * w4 + (mi & 1)) * UT_PLANE + (16 * jj + 8 * (mi >> 1) + (lane & 7)) * 16;
        uint32_t u[4], o[4];
        ldsm_x4_t(a, u[0], u[1], u[2], u[3]);
#pragma unroll
        for (int q = 0; q < 4; q++) {
            const int r = 8 * jj + 4 * (q >> 1) + 2 * (q & 1);
            o[q] = hadd2_rn(pack_bf16(acc[r], acc[r + 1]), hmul2_rn(u[q], d2));
        }
        stsm_x4_t(a, o[0], o[1], o[2], o[3]);
    }
}
__device__ __forceinline__ void aux_role(const Params& P, const CUtensorMap* mAT, const CUtensorMap* mU, const CUtensorMap* mUT, uint32_t sb, int rb, int hg) {
    const int lane = threadIdx.x & 31, w = __shfl_sync(0xffffffffu, (int)(threadIdx.x >> 5) - 8, 0), wgi = w >> 2, w4 = w & 3, t128 = threadIdx.x & 127;
    const int ch0 = 80 * hg + 5 * rb;
    aux_phase1(P, mU, mUT, sb, rb, hg, wgi, w4, lane, t128);
    const unsigned ep = threadIdx.x == 256 ? ld_relaxed(&g_cnt[(2 * 16 + hg) * 32]) : 0u;
    uint32_t dsk[3];
#pragma unroll
    for (int it = 0; it < 3; it++) dsk[it] = __ldg(reinterpret_cast<const unsigned short*>(P.Dskip) + ch0 + (it < 2 ? 2 * wgi + it : 4));
    if (lane == 0 && (w == 0 || w == 4)) TSTAMP(40 + (w >> 2));
    bar_sync(2, 256);
    aux_tables(sb, threadIdx.x - 256);
    bar_sync(2, 256);
    if (threadIdx.x == 256) TSTAMP(43);
    mbar_wait(sb + OFF_MISC + B_UT, 0);
    float acc[32];
    const uint32_t xown = sb + OFF_X + wgi * X_BYTES;
#pragma unroll 1
    for (int it = 0; it < 3 - wgi; it++) {
        const int c = it < 2 ? 2 * wgi + it : 4;
        conv_channel(acc, sb, c, w4, lane);
        if (t128 == 0) TSTAMP(44 + 4 * wgi + it);
        const uint32_t d1 = dsk[0];
        dsk[0] = dsk[1]; dsk[1] = dsk[2];
        if (w4 >= 2) conv_xput(acc, xown, w4, lane);
        bar_sync(6 + wgi, 128);
        const uint32_t ut = sb + OFF_UT + c * UT_BYTES;
        if (w4 < 2) {
            conv_xget(acc, xown, w4, lane);
            conv_finish(acc, ut, d1 | (d1 << 16), w4, lane);
        }
        bar_sync(6 + wgi, 128);
#pragma unroll
        for (int h = 0; h < 2; h++) {
            const int q = t128 + 128 * h;
            stg128(g_aT + (size_t)(ch0 + c) * SEQ + 8 * q, lds128(ut + (q & 3) * UT_PLANE + (63 - (q >> 2)) * 16));
        }
    }
    bar_sync(6 + wgi, 128);
    if (t128 == 0) {
        TSTAMP(47 + 4 * wgi);
        mbar_arrive(sb + OFF_MISC + B_CONV);
        red_release(&g_cnt[(2 * 16 + hg) * 32], 1u);
        if (wgi == 0) load_late_tiles(mAT, sb, rb, hg, ep >> 5);
    }
}
__global__ void __launch_bounds__(NTHREADS, 1)
fused_kernel(const __grid_constant__ CUtensorMap mA, const __grid_constant__ CUtensorMap mB0, const __grid_constant__ CUtensorMap mB1,
             const __grid_constant__ CUtensorMap mWo, const __grid_constant__ CUtensorMap mOut, const __grid_constant__ CUtensorMap mAT,
             const __grid_constant__ CUtensorMap mU, const __grid_constant__ CUtensorMap mUT, const __grid_constant__ CUtensorMap mO,
             const __grid_constant__ Params P) {
    extern __shared__ __align__(1024) uint8_t smem_raw[];
    const uint32_t sb = smem_u32(smem_raw);
    const int tid = threadIdx.x, warp = tid >> 5;
    const int g16 = blockIdx.x >> 4, i16 = blockIdx.x & 15;
    const int rb = (g16 & 3) * 4 + (i16 & 1) + ((i16 >> 2) & 1) * 2;
    const int hg = (g16 >> 2) * 4 + ((i16 >> 1) & 1) + (i16 >> 3) * 2;
    const uint32_t misc = sb + OFF_MISC;
    TINIT();
    if (warp >= 8) {
        asm volatile("setmaxnreg.dec.sync.aligned.u32 88;");
        if (tid == 256) TSTAMP(37);
        aux_role(P, &mAT, &mU, &mUT, sb, rb, hg);
    } else {
        if ((tid & 31) == 0) {
            if (warp < NST) {
                if (tid == 0) TSTAMP(0);
                mbar_init(misc + B_FULL + 8 * warp, 1); sts32(misc + M_STG + 4 * warp, 0);
                asm volatile("fence.mbarrier_init.release.cluster;" ::: "memory");
                issue_stage(&mA, &mB0, &mB1, sb, warp, rb, hg);
                if (tid == 0) TSTAMP(39);
            } else if (warp == 3) {
                prefetch_l2(reinterpret_cast<const uint8_t*>(P.wqkv) + blockIdx.x * 19200, 19200);
                prefetch_l2(reinterpret_cast<const uint8_t*>(P.wo) + blockIdx.x * 6400, 6400);
                TSTAMP(38);
            } else if (warp == 5) {
                mbar_init(misc + B_WO, 1); mbar_init(misc + B_GATE, 4); mbar_init(misc + B_AT, 1);
                mbar_init(misc + B_CONV, 2); mbar_init(misc + B_UT, 1);
                for (int s = 0; s < 5; s++) { mbar_init(misc + B_OF + 8 * s, 1); sts32(misc + M_OSTG + 4 * s, 0); }
                asm volatile("fence.mbarrier_init.release.cluster;" ::: "memory");
                TSTAMP(42);
            } else if (warp == 6) {
                prefetch_map(&mWo); prefetch_map(&mOut); prefetch_map(&mAT); prefetch_map(&mUT); prefetch_map(&mO);
                TSTAMP(50);
            }
        }
        __syncwarp();
        bar_sync(1, 256);
        bar_arrive(0, 512);
        if (tid == 0) TSTAMP(36);
        asm volatile("setmaxnreg.inc.sync.aligned.u32 168;");
        consumer_role(P, &mA, &mB0, &mB1, &mWo, &mOut, &mO, sb, rb, hg);
    }
    TDUMP();
}

typedef CUresult (*PFN_encodeTiled)(CUtensorMap*, CUtensorMapDataType, cuuint32_t, void*, const cuuint64_t*, const cuuint64_t*, const cuuint32_t*,
                                    const cuuint32_t*, CUtensorMapInterleave, CUtensorMapSwizzle, CUtensorMapL2promotion, CUtensorMapFloatOOBfill);
CUtensorMap make_map(PFN_encodeTiled enc, const void* base, int rank, const cuuint64_t* dims, const cuuint64_t* strides, const cuuint32_t* box, CUtensorMapSwizzle sw,
                     CUtensorMapDataType dt = CU_TENSOR_MAP_DATA_TYPE_BFLOAT16) {
    CUtensorMap m; const cuuint32_t es[5] = {1, 1, 1, 1, 1};
    enc(&m, dt, rank, const_cast<void*>(base), dims, strides, box, es, CU_TENSOR_MAP_INTERLEAVE_NONE, sw,
        CU_TENSOR_MAP_L2_PROMOTION_L2_128B, CU_TENSOR_MAP_FLOAT_OOB_FILL_NONE);
    return m;
}
long long* g_dbg_tim = nullptr;

}

extern "C" void kernel_launch(void* const* d_in, const int* in_sizes, int n_in, void* d_out, int out_size) {
    (void)in_sizes; (void)n_in; (void)out_size;
    static PFN_encodeTiled enc = nullptr;
    static void *p_o = nullptr, *p_aT = nullptr, *p_uT = nullptr;
    if (!enc) {
        void* fn = nullptr; cudaDriverEntryPointQueryResult qr;
        cudaGetDriverEntryPoint("cuTensorMapEncodeTiled", &fn, cudaEnableDefault, &qr);
        enc = (PFN_encodeTiled)fn;
        cudaGetSymbolAddress(&p_o, g_o); cudaGetSymbolAddress(&p_aT, g_aT); cudaGetSymbolAddress(&p_uT, g_uT);
        cudaFuncSetAttribute(fused_kernel, cudaFuncAttributeMaxDynamicSharedMemorySize, SMEM_BYTES);
    }
    CUtensorMap mA, mB0, mB1, mWo, mOut, mAT, mU, mUT, mO;
    { const cuuint64_t d[2] = {640, 2048}, st[1] = {1280}; const cuuint32_t b[2] = {64, 128}; mA = make_map(enc, d_in[0], 2, d, st, b, CU_TENSOR_MAP_SWIZZLE_128B); }
    { const cuuint64_t d[3] = {640, 640, 3}, st[2] = {3840, 1280}; const cuuint32_t b[3] = {64, 64, 3}, b1[3] = {16, 64, 3};
      mB0 = make_map(enc, d_in[10], 3, d, st, b, CU_TENSOR_MAP_SWIZZLE_128B); mB1 = make_map(enc, d_in[10], 3, d, st, b1, CU_TENSOR_MAP_SWIZZLE_32B); }
    { const cuuint64_t d[3] = {16, 640, 40}, st[2] = {1280, 32}; const cuuint32_t b[3] = {16, 64, 5};
      mWo = make_map(enc, d_in[11], 3, d, st, b, CU_TENSOR_MAP_SWIZZLE_32B); }
    { const cuuint64_t d[2] = {640, 2048}, st[1] = {1280}; const cuuint32_t b[2] = {80, 64};
      mOut = make_map(enc, d_out, 2, d, st, b, CU_TENSOR_MAP_SWIZZLE_NONE); }
    { const cuuint64_t d[2] = {2048, 640}, st[1] = {4096}; const cuuint32_t b[2] = {64, 80}; mAT = make_map(enc, p_aT, 2, d, st, b, CU_TENSOR_MAP_SWIZZLE_128B); }
    { const cuuint64_t d[2] = {640, 2048}, st[1] = {1280}; const cuuint32_t b[2] = {80, 128}, b1[2] = {64, 128};
      mU = make_map(enc, d_in[0], 2, d, st, b, CU_TENSOR_MAP_SWIZZLE_NONE); mO = make_map(enc, p_o, 2, d, st, b1, CU_TENSOR_MAP_SWIZZLE_128B); }
    { const cuuint64_t d[2] = {128, 2560}, st[1] = {1024}; const cuuint32_t b[2] = {148, 20};
      mUT = make_map(enc, p_uT, 2, d, st, b, CU_TENSOR_MAP_SWIZZLE_NONE, CU_TENSOR_MAP_DATA_TYPE_FLOAT64); }
    Params P;
    P.u = (const __nv_bfloat16*)d_in[0]; P.wqkv = (const __nv_bfloat16*)d_in[10]; P.wo = (const __nv_bfloat16*)d_in[11]; P.A_re = (const __nv_bfloat16*)d_in[1]; P.A_im = (const __nv_bfloat16*)d_in[2];
    P.B_re = (const __nv_bfloat16*)d_in[3]; P.B_im = (const __nv_bfloat16*)d_in[4]; P.C_re = (const __nv_bfloat16*)d_in[5];
    P.C_im = (const __nv_bfloat16*)d_in[6]; P.log_dt = (const __nv_bfloat16*)d_in[7]; P.Dskip = (const __nv_bfloat16*)d_in[8];
    P.gate_w = (const __nv_bfloat16*)d_in[12]; P.tim = g_dbg_tim;
    fused_kernel<<<128, NTHREADS, SMEM_BYTES, cudaStreamPerThread>>>(mA, mB0, mB1, mWo, mOut, mAT, mU, mUT, mO, P);
}
```
